```python
import torch

def _softmax(x, axis=-1):
    return torch.softmax(x, dim=axis)

def _gelu(x):
    return torch.nn.functional.gelu(x, approximate='tanh')

def _silu(x):
    return torch.nn.functional.silu(x)

def _sigmoid(x):
    return torch.sigmoid(x)

def _layernorm(x, axis=-1, eps=1e-05):
    m = x.mean(dim=axis, keepdim=True)
    v = x.var(dim=axis, keepdim=True, unbiased=False)
    return (x - m) / torch.sqrt(v + eps)

def _scatter_add(tgt, idx, src, axis=0):
    return tgt.clone().index_add_(axis, idx, src)

def _segment_sum(src, seg, n):
    out = torch.zeros((n,) + src.shape[1:], dtype=src.dtype)
    return out.index_add_(0, seg, src)

def _pad(x, pw):
    flat = tuple((v for pair in reversed(pw) for v in pair))
    return torch.nn.functional.pad(x, flat)
kernel_name = 'standalone__swin_window_attn__vision'

def setup_inputs():

    _w = lambda a: (lambda t: t.to(torch.bfloat16) if t.is_floating_point() else t)(torch.as_tensor(a))
    H = W = 512 // 8 * 8
    C, win = (192, 8)
    return {'x': _w((lambda *s: torch.randn(*s, dtype=torch.bfloat16) * 0.2)(1, H, W, C)), 'wqkv': _w((lambda *s: torch.randn(*s, dtype=torch.bfloat16) * 0.2)(C, 3 * C)), 'wo': _w((lambda *s: torch.randn(*s, dtype=torch.bfloat16) * 0.05)(C, C))}

def reference(x, wqkv, wo):
    B, H, W, C = x.shape
    win = 8
    nh, nw = (H // win, W // win)
    xw = (lambda x, *d: x.permute(*d))(x.reshape(B, nh, win, nw, win, C), 0, 1, 3, 2, 4, 5)
    xw = xw.reshape(B * nh * nw, win * win, C)
    qkv = xw @ wqkv
    q, k, v = (qkv[..., :C].clone(), qkv[..., C:2 * C].clone(), qkv[..., 2 * C:].clone())
    scale = C ** (-0.5)
    p = _softmax(torch.einsum('bqc,bkc->bqk', q, k) * scale, axis=-1)
    o = torch.einsum('bqk,bkc->bqc', p, v) @ wo
    o = (lambda x, *d: x.permute(*d))(o.reshape(B, nh, nw, win, win, C), 0, 1, 3, 2, 4, 5)
    return o.reshape(B, H, W, C)
```

```cpp
#include <cuda_runtime.h>
#include <cuda_bf16.h>
#include <cuda.h>
#include <stdint.h>

#define TICKET_AT 1
#define G4_PASS 11
namespace {

constexpr int kC      = 192;
constexpr int kHW     = 512;
#define MAXWIN 4096
constexpr int kNWin   = MAXWIN;
constexpr int kXBytes = 64 * kC * 2;
constexpr int kWBytes = kC * kC * 2;
constexpr int kNWG    = 3;
constexpr int kThreads = kNWG * 128;
constexpr int kTiles  = 144;
#define TRK_STEP 550
#define TRK_START 100
#define TRK_STAG 850
#define TRK_STEP0 850
#define TRK_MID 2550
#define PF_INIT 1
#define PF_LEAD 460
#define PF_UP 160
#define PF_DOWN 40
#define PF_MIN 200

constexpr int kOffWm  = 0;
constexpr int kOffWv  = kWBytes;
constexpr int kOffX   = 2 * kWBytes;
constexpr int kOffStage = kOffX + kNWG * kXBytes;
constexpr int kOffStash = kOffStage + 8192;
constexpr int kOffBar = kOffStash + 2048;
constexpr int kOffProf = kOffBar + 128;
constexpr int kSmemBytes = kOffProf;
constexpr uint32_t kSmemBase = 1024;

struct Scratch {
    uint4 img[2][2][kWBytes / 16];
    uint32_t epoch[32];
    uint32_t ticket[32];
    uint32_t cnt_v[32];
    uint32_t cnt_m[32];
};
__device__ __align__(128) Scratch g_scratch;

#define PROF(slot)
#define PROFG(slot)
#define PROFT(t, slot)
#define PROF_FLUSH()
#define STAMP(slot)
#define PSTAMP(t, slot)
#define V_AFTER 2
#define VO_DELAY 0
#define FLOG(idx)
__device__ __forceinline__ uint32_t smem_u32(const void* p) { return (uint32_t)__cvta_generic_to_shared(p); }

__device__ __forceinline__ void mbar_init(uint32_t bar, uint32_t count) {
    asm volatile("mbarrier.init.shared::cta.b64 [%0], %1;" ::"r"(bar), "r"(count) : "memory");
}
__device__ __forceinline__ void mbar_expect_tx(uint32_t bar, uint32_t bytes) {
    asm volatile("mbarrier.arrive.expect_tx.shared::cta.b64 _, [%0], %1;" ::"r"(bar), "r"(bytes) : "memory");
}
__device__ __forceinline__ void mbar_wait(uint32_t bar, uint32_t parity) {
    uint32_t ok;
    uint32_t spins = 0;
    do {
        asm volatile("{\n.reg .pred p;\n"
                     "mbarrier.try_wait.parity.shared::cta.b64 p, [%1], %2;\n"
                     "selp.b32 %0, 1, 0, p;\n}\n"
                     : "=r"(ok) : "r"(bar), "r"(parity) : "memory");
        if (++spins > (1u << 26)) __trap();
    } while (!ok);
}
__device__ __forceinline__ uint32_t tid_now() {
    uint32_t t;
    asm volatile("mov.u32 %0, %%tid.x;" : "=r"(t));
    return t;
}
__device__ __forceinline__ bool elect_one() {
    uint32_t pred;
    asm volatile("{\n.reg .pred p;\nelect.sync _|p, 0xffffffff;\nselp.b32 %0, 1, 0, p;\n}\n" : "=r"(pred));
    return pred != 0;
}
__device__ __forceinline__ uint32_t wg_uniform() { return __reduce_or_sync(0xffffffffu, tid_now() >> 7); }
constexpr uint32_t kLink = kSmemBase + kOffBar + 80;
constexpr uint32_t kSolo = 2;
__device__ __forceinline__ uint32_t baton_wait(bool wait) {
    __syncwarp();
    if (wait) asm volatile("bar.sync %0, 256;" ::"r"((tid_now() >> 7) + 8) : "memory");
    uint32_t lnk;
    asm volatile("ld.volatile.shared.u32 %0, [%1];" : "=r"(lnk) : "r"(kLink + 4 * (tid_now() >> 7)) : "memory");
    return lnk;
}
__device__ __forceinline__ void baton_pass(uint32_t lnk, uint32_t& st) {
    if (lnk != (tid_now() >> 7) + 8) asm volatile("bar.arrive %0, 256;" ::"r"(lnk) : "memory");
    else st |= kSolo;
}
__device__ __forceinline__ void set_link(int w, uint32_t v) { asm volatile("st.volatile.shared.u32 [%0], %1;" ::"r"(kLink + 4 * w), "r"(v) : "memory"); }
constexpr uint64_t kPolNormal = 0x1000000000000000ull, kPolFirst = 0x12F0000000000000ull;
__device__ __forceinline__ void tma_load_x(uint32_t dst, const CUtensorMap* tm, uint32_t bar, int win) {
    const int wh = win >> 6, ww = win & 63;
    asm volatile("cp.async.bulk.tensor.4d.shared::cluster.global.mbarrier::complete_tx::bytes"
                 " [%0], [%1, {%3, %4, %5, %6}], [%2];"
                 ::"r"(dst), "l"(tm), "r"(bar), "r"(0), "r"(ww * 8), "r"(wh * 8), "r"(0) : "memory");
}
__device__ __forceinline__ void tma_load_x_chunk(uint32_t dst, const CUtensorMap* tm, uint32_t bar, int win, int chunk) {
    const int wh = win >> 6, ww = win & 63;
    asm volatile("cp.async.bulk.tensor.4d.shared::cluster.global.mbarrier::complete_tx::bytes"
                 " [%0], [%1, {%3, %4, %5, %6}], [%2];"
                 ::"r"(dst), "l"(tm), "r"(bar), "r"(0), "r"(ww * 8), "r"(wh * 8), "r"(chunk) : "memory");
}
__device__ __forceinline__ void bulk_load(uint32_t dst, const void* src, uint32_t bytes, uint32_t bar) {
    asm volatile("cp.async.bulk.shared::cluster.global.mbarrier::complete_tx::bytes [%0], [%1], %2, [%3];"
                 ::"r"(dst), "l"(src), "r"(bytes), "r"(bar) : "memory");
}

__device__ __forceinline__ void wg_fence()  { asm volatile("wgmma.fence.sync.aligned;" ::: "memory"); }
__device__ __forceinline__ void wg_commit() { asm volatile("wgmma.commit_group.sync.aligned;" ::: "memory"); }
__device__ __forceinline__ void wg_wait0()  { asm volatile("wgmma.wait_group.sync.aligned 0;" ::: "memory"); }
__device__ __forceinline__ void wg_wait1()  { asm volatile("wgmma.wait_group.sync.aligned 1;" ::: "memory"); }

template <int N> __device__ __forceinline__ void fence_regs(float (&d)[N]) {
#pragma unroll
    for (int i = 0; i < N; i++) asm volatile("" : "+f"(d[i])::"memory");
}
template <int N> __device__ __forceinline__ void fence_regs(uint32_t (&d)[N]) {
#pragma unroll
    for (int i = 0; i < N; i++) asm volatile("" : "+r"(d[i])::"memory");
}

#define ACC8(c, d, i) c(d[i]), c(d[i + 1]), c(d[i + 2]), c(d[i + 3]), c(d[i + 4]), c(d[i + 5]), c(d[i + 6]), c(d[i + 7])
#define ACC32(c, d) ACC8(c, d, 0), ACC8(c, d, 8), ACC8(c, d, 16), ACC8(c, d, 24)
#define ACC96(c, d) ACC32(c, d), ACC8(c, d, 32), ACC8(c, d, 40), ACC8(c, d, 48), ACC8(c, d, 56), \
                    ACC8(c, d, 64), ACC8(c, d, 72), ACC8(c, d, 80), ACC8(c, d, 88)
#define C_IO(x) "+f"(x)
#define C_O(x) "=f"(x)
#define REGS32 "{%0, %1, %2, %3, %4, %5, %6, %7, %8, %9, %10, %11, %12, %13, %14, %15, " \
               "%16, %17, %18, %19, %20, %21, %22, %23, %24, %25, %26, %27, %28, %29, %30, %31}"
#define REGS96 "{%0, %1, %2, %3, %4, %5, %6, %7, %8, %9, %10, %11, %12, %13, %14, %15, " \
               "%16, %17, %18, %19, %20, %21, %22, %23, %24, %25, %26, %27, %28, %29, %30, %31, " \
               "%32, %33, %34, %35, %36, %37, %38, %39, %40, %41, %42, %43, %44, %45, %46, %47, " \
               "%48, %49, %50, %51, %52, %53, %54, %55, %56, %57, %58, %59, %60, %61, %62, %63, " \
               "%64, %65, %66, %67, %68, %69, %70, %71, %72, %73, %74, %75, %76, %77, %78, %79, " \
               "%80, %81, %82, %83, %84, %85, %86, %87, %88, %89, %90, %91, %92, %93, %94, %95}"

#define DESC_HI "0x40000040"
#define MK_DESC(name, lo, off) "add.u32 t, " lo ", " off ";\nmov.b64 " name ", {t, " DESC_HI "};\n"

template <bool First, int OA, int OB> __device__ __forceinline__ void wg192_ss(float (&d)[96], uint32_t la, uint32_t lb) {
    if constexpr (First)
        asm volatile("{\n.reg .pred p;\n.reg .b32 t;\n.reg .b64 da, db;\nsetp.ne.b32 p, 0, 0;\n"
                     MK_DESC("da", "%96", "%98") MK_DESC("db", "%97", "%99")
                     "wgmma.mma_async.sync.aligned.m64n192k16.f32.bf16.bf16 " REGS96 ", da, db, p, 1, 1, 0, 0;\n}\n"
                     : ACC96(C_O, d) : "r"(la), "r"(lb), "n"(OA), "n"(OB));
    else
        asm volatile("{\n.reg .pred p;\n.reg .b32 t;\n.reg .b64 da, db;\nsetp.ne.b32 p, 1, 0;\n"
                     MK_DESC("da", "%96", "%98") MK_DESC("db", "%97", "%99")
                     "wgmma.mma_async.sync.aligned.m64n192k16.f32.bf16.bf16 " REGS96 ", da, db, p, 1, 1, 0, 0;\n}\n"
                     : ACC96(C_IO, d) : "r"(la), "r"(lb), "n"(OA), "n"(OB));
}
template <bool First, int TB, int OB> __device__ __forceinline__ void wg192_rs(float (&d)[96], const uint32_t* a, uint32_t lb) {
    if constexpr (First)
        asm volatile("{\n.reg .pred p;\n.reg .b32 t;\n.reg .b64 db;\nsetp.ne.b32 p, 0, 0;\n"
                     MK_DESC("db", "%100", "%102")
                     "wgmma.mma_async.sync.aligned.m64n192k16.f32.bf16.bf16 " REGS96 ", {%96, %97, %98, %99}, db, p, 1, 1, %101;\n}\n"
                     : ACC96(C_O, d) : "r"(a[0]), "r"(a[1]), "r"(a[2]), "r"(a[3]), "r"(lb), "n"(TB), "n"(OB));
    else
        asm volatile("{\n.reg .pred p;\n.reg .b32 t;\n.reg .b64 db;\nsetp.ne.b32 p, 1, 0;\n"
                     MK_DESC("db", "%100", "%102")
                     "wgmma.mma_async.sync.aligned.m64n192k16.f32.bf16.bf16 " REGS96 ", {%96, %97, %98, %99}, db, p, 1, 1, %101;\n}\n"
                     : ACC96(C_IO, d) : "r"(a[0]), "r"(a[1]), "r"(a[2]), "r"(a[3]), "r"(lb), "n"(TB), "n"(OB));
}
template <bool First, int OB> __device__ __forceinline__ void wg64_rs(float (&d)[32], const uint32_t* a, uint32_t lb) {
    if constexpr (First)
        asm volatile("{\n.reg .pred p;\n.reg .b32 t;\n.reg .b64 db;\nsetp.ne.b32 p, 0, 0;\n"
                     MK_DESC("db", "%36", "%37")
                     "wgmma.mma_async.sync.aligned.m64n64k16.f32.bf16.bf16 " REGS32 ", {%32, %33, %34, %35}, db, p, 1, 1, 0;\n}\n"
                     : ACC32(C_O, d) : "r"(a[0]), "r"(a[1]), "r"(a[2]), "r"(a[3]), "r"(lb), "n"(OB));
    else
        asm volatile("{\n.reg .pred p;\n.reg .b32 t;\n.reg .b64 db;\nsetp.ne.b32 p, 1, 0;\n"
                     MK_DESC("db", "%36", "%37")
                     "wgmma.mma_async.sync.aligned.m64n64k16.f32.bf16.bf16 " REGS32 ", {%32, %33, %34, %35}, db, p, 1, 1, 0;\n}\n"
                     : ACC32(C_IO, d) : "r"(a[0]), "r"(a[1]), "r"(a[2]), "r"(a[3]), "r"(lb), "n"(OB));
}
__host__ __device__ constexpr int koff(int kk, int chunk) { return ((kk >> 2) * chunk + (kk & 3) * 32) >> 4; }

#define G1_PASS 11
#define ST_EARLY -1
__device__ __forceinline__ void stsm4(uint32_t addr, const uint4& v) {
    asm volatile("stmatrix.sync.aligned.m8n8.x4.shared.b16 [%0], {%1, %2, %3, %4};" ::"r"(addr), "r"(v.x), "r"(v.y), "r"(v.z), "r"(v.w) : "memory");
}
__device__ __forceinline__ void bulk_wait_read() { asm volatile("cp.async.bulk.wait_group.read 0;" ::: "memory"); }
template <int R> __device__ __forceinline__ void store_round(const uint4 (&h)[12], uint32_t slot, const CUtensorMap* tm, int col, int row) {
    const uint32_t l = tid_now() & 31;
    const uint32_t sa = slot + (l & 7) * 128 + (((l >> 3) ^ (l & 7)) << 4);
#pragma unroll
    for (int i = 0; i < 2; i++) {
        const int r = (2 * R + i) / 3, c = (2 * R + i) % 3;
        stsm4(sa + i * 1024, h[4 * c + r]);
        stsm4((sa ^ 64) + i * 1024, h[4 * c + 2 + r]);
    }
    asm volatile("fence.proxy.async.shared::cta;" ::: "memory");
    __syncwarp();
    asm volatile("{\n.reg .pred p;\nelect.sync _|p, 0xffffffff;\n"
                 "@p cp.async.bulk.tensor.4d.global.shared::cta.bulk_group [%0, {%2, %3, %4, %5}], [%1];\n"
                 "@p cp.async.bulk.commit_group;\n}\n"
                 ::"l"(tm + (R == 1)), "r"(slot), "r"(0), "r"(col), "r"(row + (R == 2)), "r"((int)(R == 2)) : "memory");
}
__device__ __forceinline__ uint32_t warp4_uniform() { return __reduce_or_sync(0xffffffffu, (tid_now() >> 5) & 3); }
struct OutMaps { CUtensorMap m[2]; };
constexpr uint32_t kPar = 4;
__host__ __device__ constexpr uint32_t bar_m(int c) { return kSmemBase + kOffBar + 32 + 8 * c; }
__device__ __forceinline__ void m_load(const Scratch* sc, int c, uint32_t st) {
    mbar_expect_tx(bar_m(c), 24576);
    bulk_load(kSmemBase + kOffWm + c * 24576, sc->img[(st & kPar) != 0][0] + c * 1536, 24576, bar_m(c));
}
__device__ __forceinline__ bool m_agree(uint32_t ok) {
    uint32_t all;
    asm volatile("{\n.reg .pred p, q;\nsetp.ne.u32 p, %1, 0;\nbar.red.and.pred q, 7, 256, p;\nselp.b32 %0, 1, 0, q;\n}\n" : "=r"(all) : "r"(ok) : "memory");
    return all != 0;
}
constexpr uint32_t kRound = 8;
__device__ __forceinline__ void m_check(const Scratch* sc, uint32_t st) {
    for (uint32_t round = 0;; round++) {
        uint32_t m = ~0u;
#pragma unroll 1
        for (int c = 0; c < 3; c++) {
            mbar_wait(bar_m(c), round & 1);
#pragma unroll
            for (int j = 0; j < 6; j++) {
                uint32_t v;
                asm volatile("ld.volatile.shared.b32 %0, [%1];" : "=r"(v)
                             : "r"(kSmemBase + kOffWm + c * 24576 + 4096 * j + (tid_now() & 127) * 32 + (tid_now() & 28)) : "memory");
                m = min(m, v);
            }
        }
        if (m_agree(m)) break;
        if (round > (1u << 20)) __trap();
        if (tid_now() == 128) {
            m_load(sc, 0, st); m_load(sc, 1, st); m_load(sc, 2, st);
        }
    }
}
constexpr uint32_t kBarV = kSmemBase + kOffBar + 56;
__device__ __forceinline__ void v_load(const Scratch* sc, uint32_t par) {
    mbar_expect_tx(kBarV, kWBytes);
#pragma unroll 1
    for (int c = 0; c < 3; c++) bulk_load(kSmemBase + kOffWv + c * 24576, sc->img[par][1] + c * 1536, 24576, kBarV);
}
__device__ __forceinline__ void v_check(const Scratch* sc, uint32_t par) {
    for (uint32_t round = 0;; round++) {
        mbar_wait(kBarV, round & 1);
        uint32_t m = ~0u;
#pragma unroll
        for (int j = 0; j < 18; j++) {
            uint32_t v;
            asm volatile("ld.volatile.shared.b32 %0, [%1];" : "=r"(v)
                         : "r"(kSmemBase + kOffWv + 4096 * j + (tid_now() & 127) * 32 + (tid_now() & 28)) : "memory");
            m = min(m, v);
        }
        uint32_t all;
        asm volatile("{\n.reg .pred p, q;\nsetp.ne.u32 p, %1, 0;\nbar.red.and.pred q, 14, 128, p;\nselp.b32 %0, 1, 0, q;\n}\n" : "=r"(all) : "r"(m) : "memory");
        if (all) break;
        if (round > (1u << 20)) __trap();
        if (tid_now() == 352) v_load(sc, par);
    }
}
template <int K> struct Gemm1St {
    static __device__ __forceinline__ void run(float (&d)[96], uint32_t lx, uint32_t lw, int wout, uint32_t lnk, uint32_t& st) {
        if constexpr (K > 0) Gemm1St<K - 1>::run(d, lx, lw, wout, lnk, st);
        if constexpr (K == 0 || K == 4 || K == 8) {
            if (wout < 0 && tid_now() < 128) mbar_wait(bar_m(K / 4), (st & kRound) != 0);
            wg_fence();
        }
        wg192_ss<K == 0, koff(K, 8192), koff(K, 24576)>(d, lx, lw);
        if constexpr (K == 11) wg_commit();
        if constexpr (K == G1_PASS) { if (wout >= 0 || tid_now() >= 128) baton_pass(lnk, st); }
    }
};
__device__ __forceinline__ void draw_ticket(Scratch* sc, uint32_t& ticket) {
    asm volatile("{\n.reg .pred p;\nsetp.eq.u32 p, %2, 0;\n@p atom.relaxed.gpu.global.inc.u32 %0, [%1], %3;\n}\n"
                 : "+r"(ticket) : "l"(sc->ticket), "r"(tid_now() & 127), "n"(kNWin - 1) : "memory");
}
#define G2_PASS 8
template <int KK> struct Gemm2 { static __device__ __forceinline__ void run(float (&d)[32], const uint32_t* a, uint32_t lx, uint32_t lnk, uint32_t& st) {
    Gemm2<KK - 1>::run(d, a, lx, lnk, st); wg64_rs<KK == 0, koff(KK, 8192)>(d, a + 4 * KK, lx);
    if constexpr (KK == G2_PASS) baton_pass(lnk, st); } };
template <> struct Gemm2<-1> { static __device__ __forceinline__ void run(float (&)[32], const uint32_t*, uint32_t, uint32_t, uint32_t&) {} };
template <int KK> struct Gemm3 { static __device__ __forceinline__ void run(float (&d)[96], const uint32_t* a, uint32_t lxt) {
    Gemm3<KK - 1>::run(d, a, lxt); wg192_rs<KK == 0, 1, KK * (2048 >> 4)>(d, a + 4 * KK, lxt); } };
template <> struct Gemm3<-1> { static __device__ __forceinline__ void run(float (&)[96], const uint32_t*, uint32_t) {} };
template <int K0, int KK> struct Gemm4 { static __device__ __forceinline__ void run(float (&d)[96], const uint32_t* a, uint32_t lw) {
    if constexpr (KK > K0) Gemm4<K0, KK - 1>::run(d, a, lw);
    wg192_rs<KK == 0, 0, koff(KK, 24576)>(d, a + 4 * KK, lw); } };

__device__ __forceinline__ uint32_t pack_bf16(float lo, float hi) {
    uint32_t r;
    asm("cvt.rn.bf16x2.f32 %0, %1, %2;" : "=r"(r) : "f"(hi), "f"(lo));
    return r;
}
__device__ __forceinline__ float ex2(float x) {
    float r;
    asm("ex2.approx.ftz.f32 %0, %1;" : "=f"(r) : "f"(x));
    return r;
}
__device__ __forceinline__ float rcp(float x) {
    float r;
    asm("rcp.approx.ftz.f32 %0, %1;" : "=f"(r) : "f"(x));
    return r;
}
__device__ __forceinline__ void mma16816(float (&c)[4], uint32_t a0, uint32_t a1, uint32_t a2, uint32_t a3,
                                         uint32_t b0, uint32_t b1) {
    asm volatile("mma.sync.aligned.m16n8k16.row.col.f32.bf16.bf16.f32 {%0,%1,%2,%3}, {%4,%5,%6,%7}, {%8,%9}, {%0,%1,%2,%3};"
                 : "+f"(c[0]), "+f"(c[1]), "+f"(c[2]), "+f"(c[3])
                 : "r"(a0), "r"(a1), "r"(a2), "r"(a3), "r"(b0), "r"(b1));
}

struct FoldRegs { uint4 B0[6], B1[6]; uint32_t A[48]; };

__device__ __forceinline__ void st_relaxed64(void* p, uint32_t a, uint32_t b, uint32_t on) {
    asm volatile("{\n.reg .pred q;\nsetp.ne.u32 q, %3, 0;\n@q st.relaxed.gpu.global.v2.b32 [%0], {%1, %2};\n}\n" ::"l"(p), "r"(a), "r"(b), "r"(on) : "memory");
}
__device__ __forceinline__ uint32_t pack_nonzero(float lo, float hi) { const uint32_t v = pack_bf16(lo, hi); return v != 0 ? v : 0x80000000u; }
__device__ __forceinline__ void fold_store(char* img, char* clear, uint32_t on, int n_lo, int n_hi, int k0, int q, const float (&c0)[4], const float (&c1)[4]) {
    const int u = ((k0 & 63) >> 3) + (q >> 1);
    const int base = (k0 >> 6) * 24576 + (q & 1) * 8;
    const int o_lo = base + n_lo * 128 + ((u ^ (n_lo & 7)) << 4), o_hi = base + n_hi * 128 + ((u ^ (n_hi & 7)) << 4);
    st_relaxed64(img + o_lo, pack_nonzero(c0[0], c0[1]), pack_nonzero(c1[0], c1[1]), on);
    st_relaxed64(img + o_hi, pack_nonzero(c0[2], c0[3]), pack_nonzero(c1[2], c1[3]), on);
    st_relaxed64(clear + o_lo, 0, 0, on);
    st_relaxed64(clear + o_hi, 0, 0, on);
}
__device__ __forceinline__ void fold_load_qk(FoldRegs& r, const __nv_bfloat16* __restrict__ wqkv, int tile, int lane) {
    const int g = lane >> 2, q = lane & 3;
    const int n0 = (tile / 12) * 16, k0 = (tile % 12) * 16;
    const int kb = k0 + 4 * (g >> 1) + (g & 1);
    const uint4* pa0 = reinterpret_cast<const uint4*>(wqkv + (size_t)(n0 + g) * 576 + 192 + 8 * q);
    const uint4* pa1 = reinterpret_cast<const uint4*>(wqkv + (size_t)(n0 + g + 8) * 576 + 192 + 8 * q);
    const uint4* pb0 = reinterpret_cast<const uint4*>(wqkv + (size_t)kb * 576 + 8 * q);
    const uint4* pb1 = reinterpret_cast<const uint4*>(wqkv + (size_t)(kb + 2) * 576 + 8 * q);
#pragma unroll
    for (int j = 0; j < 6; j++) {
        const uint4 lo = __ldg(pa0 + 4 * j), hi = __ldg(pa1 + 4 * j);
        r.A[8 * j + 0] = lo.x; r.A[8 * j + 1] = hi.x; r.A[8 * j + 2] = lo.y; r.A[8 * j + 3] = hi.y;
        r.A[8 * j + 4] = lo.z; r.A[8 * j + 5] = hi.z; r.A[8 * j + 6] = lo.w; r.A[8 * j + 7] = hi.w;
        r.B0[j] = __ldg(pb0 + 4 * j);
        r.B1[j] = __ldg(pb1 + 4 * j);
    }
}
__device__ __forceinline__ void fold_load_vo(FoldRegs& r, const __nv_bfloat16* __restrict__ wqkv, const __nv_bfloat16* __restrict__ wo,
                                             int tile, int lane) {
    const int g = lane >> 2, q = lane & 3;
    const int ch0 = (tile / 12) * 16 + 2 * g;
    const int k0 = (tile % 12) * 16;
    const int kb = k0 + 4 * (g >> 1) + (g & 1);
    const uint4* pb0 = reinterpret_cast<const uint4*>(wqkv + (size_t)kb * 576 + 384 + 8 * q);
    const uint4* pb1 = reinterpret_cast<const uint4*>(wqkv + (size_t)(kb + 2) * 576 + 384 + 8 * q);
    const uint32_t* pw = reinterpret_cast<const uint32_t*>(wo + (size_t)(8 * q) * kC + ch0);
#pragma unroll
    for (int j = 0; j < 6; j++) {
        r.B0[j] = __ldg(pb0 + 4 * j);
        r.B1[j] = __ldg(pb1 + 4 * j);
#pragma unroll
        for (int i = 0; i < 8; i++) r.A[8 * j + i] = __ldg(pw + (32 * j + i) * (kC / 2));
    }
}
template <bool kVO>
__device__ __forceinline__ void fold_compute_store(FoldRegs& r, Scratch* sc, int tile, int lane, uint32_t par, uint32_t on) {
    const int g = lane >> 2, q = lane & 3;
    float c0[4] = {0.f, 0.f, 0.f, 0.f}, c1[4] = {0.f, 0.f, 0.f, 0.f}, c2[4] = {0.f, 0.f, 0.f, 0.f}, c3[4] = {0.f, 0.f, 0.f, 0.f};
#pragma unroll
    for (int j = 0; j < 6; j++) {
        uint32_t a[8];
        if constexpr (kVO) {
#pragma unroll
            for (int i = 0; i < 4; i++) {
                a[2 * i]     = __byte_perm(r.A[8 * j + 2 * i], r.A[8 * j + 2 * i + 1], 0x5410);
                a[2 * i + 1] = __byte_perm(r.A[8 * j + 2 * i], r.A[8 * j + 2 * i + 1], 0x7632);
            }
        } else {
#pragma unroll
            for (int i = 0; i < 8; i++) a[i] = r.A[8 * j + i];
        }
        mma16816(c0, a[0], a[1], a[2], a[3], r.B0[j].x, r.B0[j].y);
        mma16816(c1, a[0], a[1], a[2], a[3], r.B1[j].x, r.B1[j].y);
        mma16816(c2, a[4], a[5], a[6], a[7], r.B0[j].z, r.B0[j].w);
        mma16816(c3, a[4], a[5], a[6], a[7], r.B1[j].z, r.B1[j].w);
    }
#pragma unroll
    for (int i = 0; i < 4; i++) { c0[i] += c2[i]; c1[i] += c3[i]; }
    const int k0 = (tile % 12) * 16;
    if constexpr (kVO) {
        const int n = (tile / 12) * 16 + 2 * g;
        fold_store(reinterpret_cast<char*>(sc->img[par][1]), reinterpret_cast<char*>(sc->img[par ^ 1][1]), on, n, n + 1, k0, q, c0, c1);
    } else {
        const int n0 = (tile / 12) * 16;
        fold_store(reinterpret_cast<char*>(sc->img[par][0]), reinterpret_cast<char*>(sc->img[par ^ 1][0]), on, n0 + g, n0 + g + 8, k0, q, c0, c1);
    }
}

__device__ __forceinline__ void prefetch_x(const CUtensorMap* tm, int win) {
    const int wh = win >> 6, ww = win & 63;
    asm volatile("cp.async.bulk.prefetch.tensor.3d.L2.global.tile [%0, {%1, %2, %3}];"
                 ::"l"(tm), "r"(0), "r"(ww * 8), "r"(wh * 8) : "memory");
}

__global__ void __launch_bounds__(kThreads, 1)
swin_attn_kernel(const __nv_bfloat16* __restrict__ wqkv, const __nv_bfloat16* __restrict__ wo, Scratch* __restrict__ sc,
                 const __grid_constant__ OutMaps tmo, const __grid_constant__ CUtensorMap tmx, const __grid_constant__ CUtensorMap tmp, const __grid_constant__ CUtensorMap tmc) {
    extern __shared__ uint8_t smem_raw[];
    constexpr uint32_t sbase = kSmemBase;
    if (smem_u32(smem_raw) != kSmemBase) __trap();
    const int tid = threadIdx.x, lane = tid & 31;
    const uint32_t warpu = __reduce_or_sync(0xffffffffu, (uint32_t)tid >> 5), wgu = warpu >> 2;
    const int warp = (int)warpu, wg = (int)wgu;
    const int G = gridDim.x;
    const uint32_t bar_full = sbase + kOffBar + 8 * wg;
    int win = wg * G + blockIdx.x;

    PROF(0); PROFG(1);
    if (wg == 0) FLOG(4096 + blockIdx.x * 4);
    const int ftile = blockIdx.x + (warp & 1) * G;
    FoldRegs fq;
#pragma unroll
    for (int j = 0; j < 6; j++) {
        asm volatile("" : "=r"(fq.B0[j].x), "=r"(fq.B0[j].y), "=r"(fq.B0[j].z), "=r"(fq.B0[j].w));
        asm volatile("" : "=r"(fq.B1[j].x), "=r"(fq.B1[j].y), "=r"(fq.B1[j].z), "=r"(fq.B1[j].w));
    }
#pragma unroll
    for (int j = 0; j < 48; j++) asm volatile("" : "=r"(fq.A[j]));
    if (warp < 2 && ftile < kTiles) fold_load_qk(fq, wqkv, ftile, lane);
    PSTAMP(0, 18);
    uint32_t epoch;
    asm volatile("ld.relaxed.gpu.global.u32 %0, [%1];" : "=r"(epoch) : "l"(sc->epoch) : "memory");
    if (warp == 10) {
        if (lane == 0) {
#pragma unroll
            for (int w = 0; w < kNWG; w++) mbar_init(sbase + kOffBar + 8 * w, 1);
            asm volatile("fence.mbarrier_init.release.cluster;" ::: "memory");
        }
        __syncwarp();
        asm volatile("bar.arrive 11, 384;" ::: "memory");
        if (lane == 0) {
            const uint32_t t0 = (uint32_t)clock64() + TRK_START + ((blockIdx.x * 37) & 63) * TRK_STAG / 64;
#pragma unroll
            for (int w = 0; w < kNWG; w++) mbar_expect_tx(sbase + kOffBar + 8 * w, kXBytes);
            PSTAMP(320, 18);
#pragma unroll 1
            for (int i = 0; i < 3 * kNWG + (PF_INIT > 0); i++) {
                while ((int)((uint32_t)clock64() - t0) < (i < 3 ? i * TRK_STEP0 : TRK_MID + (i - 3) * TRK_STEP)) {}
                const int w = i / 3, c = i % 3;
                if (w < kNWG) tma_load_x_chunk(sbase + kOffX + w * kXBytes + c * 8192, &tmc, sbase + kOffBar + 8 * w, w * G + blockIdx.x, c);
                else prefetch_x(&tmp, kNWG * G + blockIdx.x);
            }
        }
    }
    uint32_t st = 0;
    if (warp < 3) {
        for (int t = ftile;;) {
            const bool on = warp < 2 && t < kTiles;
            fold_compute_store<false>(fq, sc, t, lane, epoch & 1, on);
            if (lane == 0 && on) asm volatile("red.relaxed.gpu.global.add.u32 [%0], %1;" ::"l"(sc->cnt_m), "r"(1u) : "memory");
            PSTAMP(0, 20);
            t += 2 * G;
            if (__builtin_expect(warp == 2 || t >= kTiles, 1)) break;
            fold_load_qk(fq, wqkv, t, lane);
        }
    }
    if (warp < 4) {
        asm volatile("bar.sync 11, 384;" ::: "memory");
    } else if (warp == 4) {
        if (lane == 0) {
            set_link(0, 9); set_link(1, 8); set_link(2, 8);
            mbar_init(bar_m(0), 1);
            mbar_init(bar_m(1), 1);
            mbar_init(bar_m(2), 1);
            asm volatile("fence.mbarrier_init.release.cluster;" ::: "memory");
        }
        __syncwarp();
        asm volatile("bar.arrive 12, 128;" ::: "memory");
        asm volatile("bar.arrive 11, 384;" ::: "memory");
        if (lane == 0) {
            uint32_t v, spins = 0;
            do {
                asm volatile("ld.relaxed.gpu.global.u32 %0, [%1];" : "=r"(v) : "l"(sc->cnt_m) : "memory");
                if (++spins > (1u << 22)) __trap();
            } while (v < kTiles);
            PSTAMP(128, 21);
            const uint32_t par = (epoch & 1) * kPar;
            m_load(sc, 0, par); m_load(sc, 1, par); m_load(sc, 2, par);
            PSTAMP(128, 22);
        }
    } else if (warp == 11) {
        if (lane == 0) {
            mbar_init(kBarV, 1);
            asm volatile("fence.mbarrier_init.release.cluster;" ::: "memory");
        }
        __syncwarp();
        asm volatile("bar.sync 11, 384;" ::: "memory");
        if (lane == 0) {
            uint32_t v, spins = 0;
            do {
                asm volatile("ld.relaxed.gpu.global.u32 %0, [%1];" : "=r"(v) : "l"(sc->cnt_v) : "memory");
                if (++spins > (1u << 22)) __trap();
            } while (v < kTiles);
            PSTAMP(352, 23);
            { uint32_t ok = 0, n = 0;
              while (!ok && ++n < 64) asm volatile("{\n.reg .pred p;\nmbarrier.try_wait.parity.shared::cta.b64 p, [%1], 0;\nselp.b32 %0, 1, 0, p;\n}\n" : "=r"(ok) : "r"(bar_m(V_AFTER)) : "memory"); }
            v_load(sc, epoch & 1);
            PSTAMP(352, 24);
        }
    } else if (warp == 10) {
    } else if (warp >= 8) {
        asm volatile("bar.arrive 11, 384;" ::: "memory");
        { const uint32_t t0 = (uint32_t)clock64(); while ((uint32_t)clock64() - t0 < VO_DELAY) {} }
        FoldRegs fr;
        for (int t = G - 1 - blockIdx.x + (warp & 1) * G; t < kTiles; t += 2 * G) {
            fold_load_vo(fr, wqkv, wo, t, lane);
            fold_compute_store<true>(fr, sc, t, lane, epoch & 1, 1);
            PSTAMP(256, 18);
            if (lane == 0) asm volatile("red.relaxed.gpu.global.add.u32 [%0], %1;" ::"l"(sc->cnt_v), "r"(1u) : "memory");
            PSTAMP(256, 19);
        }
    } else {
        asm volatile("bar.arrive 11, 384;" ::: "memory");
        asm volatile("bar.sync 12, 128;" ::: "memory");
    }
    __syncwarp();
    if (wg == 1) m_check(sc, (epoch & 1) * kPar);
    uint4 hv[12];
#pragma unroll
    for (int a = 0; a < 12; a++) asm volatile("" : "=r"(hv[a].x), "=r"(hv[a].y), "=r"(hv[a].z), "=r"(hv[a].w));

    constexpr uint32_t dWm = ((sbase + kOffWm) >> 4) | (1u << 16);
    constexpr uint32_t dWv = ((sbase + kOffWv) >> 4) | (1u << 16);
    const float cs = 0.07216878364870322f * 1.4426950408889634f;
    PROF(2);
    PSTAMP(0, 23);
    PROF(3);
    if (wg == 2) {
        asm volatile("bar.sync 13, 128;" ::: "memory");
        v_check(sc, epoch & 1);
        PSTAMP(256, 23);
    }
    mbar_wait(bar_full, 0);
    PSTAMP(0, 24); PSTAMP(128, 24); PSTAMP(256, 24);

    int wout = -1;

    while (true) {
        float acc[96];
        uint32_t fa[48];
        const uint32_t dX = ((sbase + kOffX + wg_uniform() * kXBytes) >> 4) | (1u << 16);
        uint32_t ticket = 0;
        STAMP(0);
        uint32_t lnk = baton_wait(wout >= 0 ? !(st & kSolo) : tid_now() >= 128);
        STAMP(1);
        while (true) {
            Gemm1St<11>::run(acc, dX, dWm, wout, lnk, st);
            if (wout >= 0 || tid_now() >= 128) break;
            wg_wait0();
            if (m_agree(1)) break;
            st ^= kRound;
        }
        STAMP(2);
        if (wout >= 0) {
            const uint32_t w4 = warp4_uniform();
            const uint32_t slot = sbase + kOffStage + w4 * 2048;
            const int col = (wout & 63) * 8, row = (wout >> 6) * 8 + 2 * w4;
            store_round<0>(hv, slot, tmo.m, col, row);
            bulk_wait_read(); __syncwarp();
            store_round<1>(hv, slot, tmo.m, col, row);
            bulk_wait_read(); __syncwarp();
            store_round<2>(hv, slot, tmo.m, col, row);
        }
        draw_ticket(&g_scratch, ticket);
        wg_wait0();
        STAMP(3);
        fence_regs(acc);
#pragma unroll
        for (int i = 0; i < 48; i++) fa[i] = pack_bf16(acc[2 * i], acc[2 * i + 1]);

        float s[32];
        fence_regs(fa);
        __syncwarp();
        bulk_wait_read();
        __syncwarp(); STAMP(4);
        lnk = baton_wait(wout >= 0 ? !(st & kSolo) : tid_now() >= 128);
        STAMP(5);
        wg_fence();
        Gemm2<11>::run(s, fa, dX, lnk, st);
        wg_commit();
        STAMP(6);
        wg_wait0();
        FLOG(win);
        STAMP(7);
        fence_regs(s);
        fence_regs(fa);

        uint32_t pa[16];
        {
            float a0[8], a1[8];
#pragma unroll
            for (int j = 0; j < 8; j++) { a0[j] = fmaxf(s[4 * j], s[4 * j + 1]); a1[j] = fmaxf(s[4 * j + 2], s[4 * j + 3]); }
#pragma unroll
            for (int d = 4; d > 0; d >>= 1)
#pragma unroll
                for (int j = 0; j < d; j++) { a0[j] = fmaxf(a0[j], a0[j + d]); a1[j] = fmaxf(a1[j], a1[j + d]); }
            float m0 = a0[0], m1 = a1[0];
            m0 = fmaxf(m0, __shfl_xor_sync(0xffffffffu, m0, 1));
            m1 = fmaxf(m1, __shfl_xor_sync(0xffffffffu, m1, 1));
            m0 = fmaxf(m0, __shfl_xor_sync(0xffffffffu, m0, 2));
            m1 = fmaxf(m1, __shfl_xor_sync(0xffffffffu, m1, 2));
            m0 *= cs; m1 *= cs;
            float l0 = 0.f, l1 = 0.f;
#pragma unroll
            for (int j = 0; j < 8; j++) {
                s[4 * j]     = ex2(fmaf(s[4 * j], cs, -m0));
                s[4 * j + 1] = ex2(fmaf(s[4 * j + 1], cs, -m0));
                s[4 * j + 2] = ex2(fmaf(s[4 * j + 2], cs, -m1));
                s[4 * j + 3] = ex2(fmaf(s[4 * j + 3], cs, -m1));
                l0 += s[4 * j] + s[4 * j + 1];
                l1 += s[4 * j + 2] + s[4 * j + 3];
            }
            l0 += __shfl_xor_sync(0xffffffffu, l0, 1);
            l1 += __shfl_xor_sync(0xffffffffu, l1, 1);
            l0 += __shfl_xor_sync(0xffffffffu, l0, 2);
            l1 += __shfl_xor_sync(0xffffffffu, l1, 2);
            const float r0 = rcp(l0), r1 = rcp(l1);
#pragma unroll
            for (int j = 0; j < 8; j++) {
                pa[2 * j]     = pack_bf16(s[4 * j] * r0, s[4 * j + 1] * r0);
                pa[2 * j + 1] = pack_bf16(s[4 * j + 2] * r1, s[4 * j + 3] * r1);
            }
        }

        fence_regs(pa);
        __syncwarp(); STAMP(8);
        lnk = baton_wait(!(st & kSolo));
        if (wout < 0 && tid_now() == 0) set_link(1, 10);
        STAMP(9);
        wg_fence();
        Gemm3<3>::run(acc, pa, ((sbase + kOffX + wg_uniform() * kXBytes) >> 4) | ((8192u >> 4) << 16));
        wg_commit();
        baton_pass(lnk, st);
        STAMP(10);
        const int nxt = kNWG * (int)gridDim.x + (int)__reduce_or_sync(0xffffffffu, ticket);
        wg_wait0();
        STAMP(11);
        fence_regs(acc);
        fence_regs(pa);

        if (((tid_now() >> 5) & 3) == 0 && nxt < kNWin) {
            asm volatile("bar.sync %0, 128;" ::"r"((tid_now() >> 7) + 1) : "memory");
            if (elect_one()) {
                const uint32_t wgl = tid_now() >> 7;
                const uint32_t bar = sbase + kOffBar + 8 * wgl;
                mbar_expect_tx(bar, kXBytes);
                tma_load_x(sbase + kOffX + wgl * kXBytes, &tmx, bar, nxt);
            }
            __syncwarp();
        } else {
            asm volatile("bar.arrive %0, 128;" ::"r"((tid_now() >> 7) + 1) : "memory");
        }
#pragma unroll
        for (int i = 0; i < 48; i++) fa[i] = pack_bf16(acc[2 * i], acc[2 * i + 1]);

        asm volatile("st.volatile.shared.v4.b32 [%4], {%0, %1, %2, %3};"
                     :: "r"(fa[44]), "r"(fa[45]), "r"(fa[46]), "r"(fa[47]), "r"(sbase + kOffStash + (tid_now() & 127) * 16) : "memory");
        fence_regs(fa);
        __syncwarp(); STAMP(12);
        lnk = baton_wait(!(st & kSolo));
        STAMP(13);
        if ((tid_now() & 127) == 0) {
            if (nxt >= kNWin) {
#pragma unroll
                for (int w = 0; w < kNWG; w++) {
                    uint32_t l;
                    asm volatile("ld.volatile.shared.u32 %0, [%1];" : "=r"(l) : "r"(kLink + 4 * w) : "memory");
                    if (l == (tid_now() >> 7) + 8) set_link(w, lnk);
                }
            }
            asm volatile("st.shared.u32 [%0], %1;" ::"r"(sbase + kOffBar + 64 + 4 * (tid_now() >> 7)), "r"(nxt) : "memory");
        }
        __syncwarp();
        wg_fence();
        Gemm4<0, 1>::run(acc, fa, dWv);
        wg_commit();
        Gemm4<2, 10>::run(acc, fa, dWv);
        wg_commit();
        wg_wait1();
        uint32_t fl[4];
        asm volatile("ld.volatile.shared.v4.b32 {%0, %1, %2, %3}, [%4];"
                     : "=r"(fl[0]), "=r"(fl[1]), "=r"(fl[2]), "=r"(fl[3]) : "r"(sbase + kOffStash + (tid_now() & 127) * 16) : "memory");
        wg_fence();
        wg192_rs<false, 0, koff(11, 24576)>(acc, fl, dWv);
        wg_commit();
        baton_pass(lnk, st);
        STAMP(14);
        if (((tid_now() >> 5) & 3) == 0) {
            asm volatile("bar.arrive %0, 128;" ::"r"((tid_now() >> 7) + 4) : "memory");
            if (elect_one()) {
                const int base = kNWG * (int)gridDim.x, t = nxt - base;
                auto lead = [&](int tt) { return min(min(PF_INIT * (int)gridDim.x + ((tt * PF_UP) >> 8), PF_LEAD), max(((kNWin - base - tt) * PF_DOWN) >> 8, PF_MIN)); };
                const int hi = base + t + lead(t);
                int lo = max(max(base + t - 1 + lead(t - 1), base + t) + 1, base + PF_INIT * (int)gridDim.x);
#pragma unroll 1
                for (; lo <= hi && lo < kNWin; lo++) prefetch_x(&tmp, lo);
                if (t == kNWin - 1) { g_scratch.cnt_v[0] = 0; g_scratch.cnt_m[0] = 0; atomicAdd(g_scratch.epoch, 1); }
            }
            __syncwarp();
        } else {
            asm volatile("bar.sync %0, 128;" ::"r"((tid_now() >> 7) + 4) : "memory");
        }
        uint32_t pub;
        asm volatile("ld.shared.u32 %0, [%1];" : "=r"(pub) : "r"(sbase + kOffBar + 64 + 4 * (tid_now() >> 7)) : "memory");
        const int win_next = (int)__reduce_or_sync(0xffffffffu, pub);
        st ^= 1;
        if (win_next < kNWin) mbar_wait(sbase + kOffBar + 8 * (tid_now() >> 7), st & 1);
        wg_wait0();
        STAMP(15);
        fence_regs(acc);
        fence_regs(fa);
        fence_regs(fl);

        {
            wout = win;
#pragma unroll
            for (int a = 0; a < 6; a++) {
                hv[2 * a].x     = pack_bf16(acc[16 * a + 0], acc[16 * a + 1]);
                hv[2 * a].y     = pack_bf16(acc[16 * a + 4], acc[16 * a + 5]);
                hv[2 * a].z     = pack_bf16(acc[16 * a + 8], acc[16 * a + 9]);
                hv[2 * a].w     = pack_bf16(acc[16 * a + 12], acc[16 * a + 13]);
                hv[2 * a + 1].x = pack_bf16(acc[16 * a + 2], acc[16 * a + 3]);
                hv[2 * a + 1].y = pack_bf16(acc[16 * a + 6], acc[16 * a + 7]);
                hv[2 * a + 1].z = pack_bf16(acc[16 * a + 10], acc[16 * a + 11]);
                hv[2 * a + 1].w = pack_bf16(acc[16 * a + 14], acc[16 * a + 15]);
            }
        }
        STAMP(16);
        win = win_next;
        if (win >= kNWin) break;
    }
    asm volatile("bar.sync %0, 128;" ::"r"((tid_now() >> 7) + 1) : "memory");
    {
        const uint32_t w4 = warp4_uniform();
        const uint32_t slot = sbase + kOffX + wg_uniform() * kXBytes + w4 * 6144;
        const int col = (wout & 63) * 8, row = (wout >> 6) * 8 + 2 * w4;
        store_round<0>(hv, slot, tmo.m, col, row);
        store_round<1>(hv, slot + 2048, tmo.m, col, row);
        store_round<2>(hv, slot + 4096, tmo.m, col, row);
    }
    bulk_wait_read();
    FLOG(4096 + blockIdx.x * 4 + 1 + (tid_now() >> 7));
    PROF(4); PROFG(5);
    PROF_FLUSH();
}

typedef CUresult (*EncodeTiledFn)(CUtensorMap*, CUtensorMapDataType, cuuint32_t, void*, const cuuint64_t*,
                                  const cuuint64_t*, const cuuint32_t*, const cuuint32_t*, CUtensorMapInterleave,
                                  CUtensorMapSwizzle, CUtensorMapL2promotion, CUtensorMapFloatOOBfill);

}

extern "C" void kernel_launch(void* const* d_in, const int* in_sizes, int n_in, void* d_out, int out_size) {
    (void)in_sizes; (void)n_in; (void)out_size;
    const __nv_bfloat16* x    = (const __nv_bfloat16*)d_in[0];
    const __nv_bfloat16* wqkv = (const __nv_bfloat16*)d_in[1];
    const __nv_bfloat16* wo   = (const __nv_bfloat16*)d_in[2];

    static EncodeTiledFn encode = nullptr;
    static int num_sms = 0;
    static Scratch* scratch = nullptr;
    if (!encode) {
        void* fn = nullptr;
        cudaDriverEntryPointQueryResult qr;
        cudaGetDriverEntryPoint("cuTensorMapEncodeTiled", &fn, cudaEnableDefault, &qr);
        encode = (EncodeTiledFn)fn;
        cudaGetSymbolAddress((void**)&scratch, g_scratch);
        int dev = 0;
        cudaGetDevice(&dev);
        cudaDeviceGetAttribute(&num_sms, cudaDevAttrMultiProcessorCount, dev);
        cudaFuncSetAttribute(swin_attn_kernel, cudaFuncAttributeMaxDynamicSharedMemorySize, kSmemBytes);
    }
    CUtensorMap tmx;
    const cuuint64_t gdim[4] = {64, (cuuint64_t)kHW, (cuuint64_t)kHW, 3};
    const cuuint64_t gstr[3] = {(cuuint64_t)kC * 2, (cuuint64_t)kHW * kC * 2, 128};
    const cuuint32_t box[4] = {64, 8, 8, 3};
    const cuuint32_t estr[4] = {1, 1, 1, 1};
    encode(&tmx, CU_TENSOR_MAP_DATA_TYPE_BFLOAT16, 4, (void*)x, gdim, gstr, box, estr, CU_TENSOR_MAP_INTERLEAVE_NONE,
           CU_TENSOR_MAP_SWIZZLE_128B, CU_TENSOR_MAP_L2_PROMOTION_NONE, CU_TENSOR_MAP_FLOAT_OOB_FILL_NONE);

    CUtensorMap tmp;
    const cuuint64_t pdim[3] = {(cuuint64_t)kC, (cuuint64_t)kHW, (cuuint64_t)kHW};
    const cuuint64_t pstr[2] = {(cuuint64_t)kC * 2, (cuuint64_t)kHW * kC * 2};
    const cuuint32_t pbox[3] = {(cuuint32_t)kC, 8, 8};
    encode(&tmp, CU_TENSOR_MAP_DATA_TYPE_BFLOAT16, 3, (void*)x, pdim, pstr, pbox, estr, CU_TENSOR_MAP_INTERLEAVE_NONE,
           CU_TENSOR_MAP_SWIZZLE_NONE, CU_TENSOR_MAP_L2_PROMOTION_NONE, CU_TENSOR_MAP_FLOAT_OOB_FILL_NONE);
    CUtensorMap tmc;
    const cuuint32_t boxc[4] = {64, 8, 8, 1};
    encode(&tmc, CU_TENSOR_MAP_DATA_TYPE_BFLOAT16, 4, (void*)x, gdim, gstr, boxc, estr, CU_TENSOR_MAP_INTERLEAVE_NONE,
           CU_TENSOR_MAP_SWIZZLE_128B, CU_TENSOR_MAP_L2_PROMOTION_NONE, CU_TENSOR_MAP_FLOAT_OOB_FILL_NONE);
    OutMaps tmo;
    const cuuint32_t boxo[4] = {64, 8, 1, 2};
    encode(&tmo.m[0], CU_TENSOR_MAP_DATA_TYPE_BFLOAT16, 4, d_out, gdim, gstr, boxo, estr, CU_TENSOR_MAP_INTERLEAVE_NONE,
           CU_TENSOR_MAP_SWIZZLE_128B, CU_TENSOR_MAP_L2_PROMOTION_NONE, CU_TENSOR_MAP_FLOAT_OOB_FILL_NONE);
    const cuuint64_t odim[4] = {64, (cuuint64_t)kHW, (cuuint64_t)kHW, 2};
    const cuuint64_t ostr[3] = {(cuuint64_t)kC * 2, (cuuint64_t)kHW * kC * 2, (cuuint64_t)kHW * kC * 2 - 256};
    encode(&tmo.m[1], CU_TENSOR_MAP_DATA_TYPE_BFLOAT16, 4, (char*)d_out + 256, odim, ostr, boxo, estr, CU_TENSOR_MAP_INTERLEAVE_NONE,
           CU_TENSOR_MAP_SWIZZLE_128B, CU_TENSOR_MAP_L2_PROMOTION_NONE, CU_TENSOR_MAP_FLOAT_OOB_FILL_NONE);
    swin_attn_kernel<<<num_sms, kThreads, kSmemBytes, cudaStreamPerThread>>>(wqkv, wo, scratch, tmo, tmx, tmp, tmc);
}
```

```cpp
#include <cuda_runtime.h>
#include <cuda_bf16.h>
#include <cuda.h>
#include <stdint.h>

#define TICKET_AT 1
#define G4_PASS 11
namespace {

constexpr int kC      = 192;
constexpr int kHW     = 512;
#define MAXWIN 4096
constexpr int kNWin   = MAXWIN;
constexpr int kXBytes = 64 * kC * 2;
constexpr int kWBytes = kC * kC * 2;
constexpr int kNWG    = 3;
constexpr int kThreads = kNWG * 128;
constexpr int kTiles  = 144;
#define TRK_STEP 550
#define TRK_START 100
#define TRK_STAG 850
#define TRK_STEP0 850
#define TRK_MID 2550
#define PF_INIT 2
#define PF_LEAD 420
#define PF_UP 160
#define PF_DOWN 36
#define PF_MIN 200

constexpr int kOffWm  = 0;
constexpr int kOffWv  = kWBytes;
constexpr int kOffX   = 2 * kWBytes;
constexpr int kOffStage = kOffX + kNWG * kXBytes;
constexpr int kOffStash = kOffStage + 8192;
constexpr int kOffBar = kOffStash + 2048;
constexpr int kOffProf = kOffBar + 128;
constexpr int kSmemBytes = kOffProf;
constexpr uint32_t kSmemBase = 1024;

struct Scratch {
    uint32_t ticket[32];
    uint32_t epoch[32];
    uint32_t cnt_v[32];
    uint32_t cnt_m[32];
    uint4 img[2][2][kWBytes / 16];
};
__device__ __align__(128) Scratch g_scratch;

#define PROF(slot)
#define PROFG(slot)
#define PROFT(t, slot)
#define PROF_FLUSH()
#define STAMP(slot)
#define PSTAMP(t, slot)
#define V_AFTER 2
#define VO_DELAY 0
#define FLOG(idx)
__device__ __forceinline__ uint32_t smem_u32(const void* p) { return (uint32_t)__cvta_generic_to_shared(p); }

__device__ __forceinline__ void mbar_init(uint32_t bar, uint32_t count) {
    asm volatile("mbarrier.init.shared::cta.b64 [%0], %1;" ::"r"(bar), "r"(count) : "memory");
}
__device__ __forceinline__ void mbar_expect_tx(uint32_t bar, uint32_t bytes) {
    asm volatile("mbarrier.arrive.expect_tx.shared::cta.b64 _, [%0], %1;" ::"r"(bar), "r"(bytes) : "memory");
}
__device__ __forceinline__ void mbar_wait(uint32_t bar, uint32_t parity) {
    uint32_t ok;
    uint32_t spins = 0;
    do {
        asm volatile("{\n.reg .pred p;\n"
                     "mbarrier.try_wait.parity.shared::cta.b64 p, [%1], %2;\n"
                     "selp.b32 %0, 1, 0, p;\n}\n"
                     : "=r"(ok) : "r"(bar), "r"(parity) : "memory");
        if (++spins > (1u << 26)) __trap();
    } while (!ok);
}
__device__ __forceinline__ uint32_t tid_now() {
    uint32_t t;
    asm volatile("mov.u32 %0, %%tid.x;" : "=r"(t));
    return t;
}
__device__ __forceinline__ bool elect_one() {
    uint32_t pred;
    asm volatile("{\n.reg .pred p;\nelect.sync _|p, 0xffffffff;\nselp.b32 %0, 1, 0, p;\n}\n" : "=r"(pred));
    return pred != 0;
}
__device__ __forceinline__ uint32_t wg_uniform() { return __reduce_or_sync(0xffffffffu, tid_now() >> 7); }
constexpr uint32_t kLink = kSmemBase + kOffBar + 80;
constexpr uint32_t kPhase = 1;
constexpr uint32_t kSolo = 2;
constexpr uint32_t kFirst = 4;
constexpr uint32_t kRound = 8;
__device__ __forceinline__ int st_out(uint32_t st) { return (st >> 4) & 0x1fff; }
__device__ __forceinline__ int st_win(uint32_t st) { return st >> 17; }
__device__ __forceinline__ uint32_t baton_wait(uint32_t st, uint32_t packed) {
    if (packed == 0xffffffffu) __trap();
    if (!(st & kSolo)) asm volatile("bar.sync %0, 256;" ::"r"((tid_now() >> 7) + 8) : "memory");
    uint32_t lnk;
    asm volatile("ld.volatile.shared.u32 %0, [%1];" : "=r"(lnk) : "r"(kLink + 4 * (tid_now() >> 7)) : "memory");
    return lnk;
}
__device__ __forceinline__ void baton_pass(uint32_t lnk, uint32_t& st) {
    const bool other = lnk != (tid_now() >> 7) + 8;
    if (other) asm volatile("bar.arrive %0, 256;" ::"r"(lnk) : "memory");
    st = other ? st & ~kSolo : st | kSolo;
}
__device__ __forceinline__ void set_link(int w, uint32_t v) { asm volatile("st.volatile.shared.u32 [%0], %1;" ::"r"(kLink + 4 * w), "r"(v) : "memory"); }
#define LD_EF_FROM 3100
constexpr uint64_t kPolNormal = 0x1000000000000000ull, kPolFirst = 0x12F0000000000000ull;
__device__ __forceinline__ void tma_load_x(uint32_t dst, const CUtensorMap* tm, uint32_t bar, int win) {
    const int wh = win >> 6, ww = win & 63;
    asm volatile("cp.async.bulk.tensor.4d.shared::cluster.global.mbarrier::complete_tx::bytes.L2::cache_hint"
                 " [%0], [%1, {%3, %4, %5, %6}], [%2], %7;"
                 ::"r"(dst), "l"(tm), "r"(bar), "r"(0), "r"(ww * 8), "r"(wh * 8), "r"(0), "l"(win >= LD_EF_FROM ? kPolFirst : kPolNormal) : "memory");
}
__device__ __forceinline__ void tma_load_x_chunk(uint32_t dst, const CUtensorMap* tm, uint32_t bar, int win, int chunk) {
    const int wh = win >> 6, ww = win & 63;
    asm volatile("cp.async.bulk.tensor.4d.shared::cluster.global.mbarrier::complete_tx::bytes"
                 " [%0], [%1, {%3, %4, %5, %6}], [%2];"
                 ::"r"(dst), "l"(tm), "r"(bar), "r"(0), "r"(ww * 8), "r"(wh * 8), "r"(chunk) : "memory");
}
__device__ __forceinline__ void bulk_load(uint32_t dst, const void* src, uint32_t bytes, uint32_t bar) {
    asm volatile("cp.async.bulk.shared::cluster.global.mbarrier::complete_tx::bytes [%0], [%1], %2, [%3];"
                 ::"r"(dst), "l"(src), "r"(bytes), "r"(bar) : "memory");
}

__device__ __forceinline__ void wg_fence()  { asm volatile("wgmma.fence.sync.aligned;" ::: "memory"); }
__device__ __forceinline__ void wg_commit() { asm volatile("wgmma.commit_group.sync.aligned;" ::: "memory"); }
__device__ __forceinline__ void wg_wait0()  { asm volatile("wgmma.wait_group.sync.aligned 0;" ::: "memory"); }
__device__ __forceinline__ void wg_wait1()  { asm volatile("wgmma.wait_group.sync.aligned 1;" ::: "memory"); }

template <int N> __device__ __forceinline__ void fence_regs(float (&d)[N]) {
#pragma unroll
    for (int i = 0; i < N; i++) asm volatile("" : "+f"(d[i])::"memory");
}
template <int N> __device__ __forceinline__ void fence_regs(uint32_t (&d)[N]) {
#pragma unroll
    for (int i = 0; i < N; i++) asm volatile("" : "+r"(d[i])::"memory");
}

#define ACC8(c, d, i) c(d[i]), c(d[i + 1]), c(d[i + 2]), c(d[i + 3]), c(d[i + 4]), c(d[i + 5]), c(d[i + 6]), c(d[i + 7])
#define ACC32(c, d) ACC8(c, d, 0), ACC8(c, d, 8), ACC8(c, d, 16), ACC8(c, d, 24)
#define ACC96(c, d) ACC32(c, d), ACC8(c, d, 32), ACC8(c, d, 40), ACC8(c, d, 48), ACC8(c, d, 56), \
                    ACC8(c, d, 64), ACC8(c, d, 72), ACC8(c, d, 80), ACC8(c, d, 88)
#define C_IO(x) "+f"(x)
#define C_O(x) "=f"(x)
#define REGS32 "{%0, %1, %2, %3, %4, %5, %6, %7, %8, %9, %10, %11, %12, %13, %14, %15, " \
               "%16, %17, %18, %19, %20, %21, %22, %23, %24, %25, %26, %27, %28, %29, %30, %31}"
#define REGS96 "{%0, %1, %2, %3, %4, %5, %6, %7, %8, %9, %10, %11, %12, %13, %14, %15, " \
               "%16, %17, %18, %19, %20, %21, %22, %23, %24, %25, %26, %27, %28, %29, %30, %31, " \
               "%32, %33, %34, %35, %36, %37, %38, %39, %40, %41, %42, %43, %44, %45, %46, %47, " \
               "%48, %49, %50, %51, %52, %53, %54, %55, %56, %57, %58, %59, %60, %61, %62, %63, " \
               "%64, %65, %66, %67, %68, %69, %70, %71, %72, %73, %74, %75, %76, %77, %78, %79, " \
               "%80, %81, %82, %83, %84, %85, %86, %87, %88, %89, %90, %91, %92, %93, %94, %95}"

#define DESC_HI "0x40000040"
#define MK_DESC(name, lo, off) "add.u32 t, " lo ", " off ";\nmov.b64 " name ", {t, " DESC_HI "};\n"

template <bool First, int OA, int OB> __device__ __forceinline__ void wg192_ss(float (&d)[96], uint32_t la, uint32_t lb) {
    if constexpr (First)
        asm volatile("{\n.reg .pred p;\n.reg .b32 t;\n.reg .b64 da, db;\nsetp.ne.b32 p, 0, 0;\n"
                     MK_DESC("da", "%96", "%98") MK_DESC("db", "%97", "%99")
                     "wgmma.mma_async.sync.aligned.m64n192k16.f32.bf16.bf16 " REGS96 ", da, db, p, 1, 1, 0, 0;\n}\n"
                     : ACC96(C_O, d) : "r"(la), "r"(lb), "n"(OA), "n"(OB));
    else
        asm volatile("{\n.reg .pred p;\n.reg .b32 t;\n.reg .b64 da, db;\nsetp.ne.b32 p, 1, 0;\n"
                     MK_DESC("da", "%96", "%98") MK_DESC("db", "%97", "%99")
                     "wgmma.mma_async.sync.aligned.m64n192k16.f32.bf16.bf16 " REGS96 ", da, db, p, 1, 1, 0, 0;\n}\n"
                     : ACC96(C_IO, d) : "r"(la), "r"(lb), "n"(OA), "n"(OB));
}
template <bool First, int TB, int OB> __device__ __forceinline__ void wg192_rs(float (&d)[96], const uint32_t* a, uint32_t lb) {
    if constexpr (First)
        asm volatile("{\n.reg .pred p;\n.reg .b32 t;\n.reg .b64 db;\nsetp.ne.b32 p, 0, 0;\n"
                     MK_DESC("db", "%100", "%102")
                     "wgmma.mma_async.sync.aligned.m64n192k16.f32.bf16.bf16 " REGS96 ", {%96, %97, %98, %99}, db, p, 1, 1, %101;\n}\n"
                     : ACC96(C_O, d) : "r"(a[0]), "r"(a[1]), "r"(a[2]), "r"(a[3]), "r"(lb), "n"(TB), "n"(OB));
    else
        asm volatile("{\n.reg .pred p;\n.reg .b32 t;\n.reg .b64 db;\nsetp.ne.b32 p, 1, 0;\n"
                     MK_DESC("db", "%100", "%102")
                     "wgmma.mma_async.sync.aligned.m64n192k16.f32.bf16.bf16 " REGS96 ", {%96, %97, %98, %99}, db, p, 1, 1, %101;\n}\n"
                     : ACC96(C_IO, d) : "r"(a[0]), "r"(a[1]), "r"(a[2]), "r"(a[3]), "r"(lb), "n"(TB), "n"(OB));
}
template <bool First, int OB> __device__ __forceinline__ void wg64_rs(float (&d)[32], const uint32_t* a, uint32_t lb) {
    if constexpr (First)
        asm volatile("{\n.reg .pred p;\n.reg .b32 t;\n.reg .b64 db;\nsetp.ne.b32 p, 0, 0;\n"
                     MK_DESC("db", "%36", "%37")
                     "wgmma.mma_async.sync.aligned.m64n64k16.f32.bf16.bf16 " REGS32 ", {%32, %33, %34, %35}, db, p, 1, 1, 0;\n}\n"
                     : ACC32(C_O, d) : "r"(a[0]), "r"(a[1]), "r"(a[2]), "r"(a[3]), "r"(lb), "n"(OB));
    else
        asm volatile("{\n.reg .pred p;\n.reg .b32 t;\n.reg .b64 db;\nsetp.ne.b32 p, 1, 0;\n"
                     MK_DESC("db", "%36", "%37")
                     "wgmma.mma_async.sync.aligned.m64n64k16.f32.bf16.bf16 " REGS32 ", {%32, %33, %34, %35}, db, p, 1, 1, 0;\n}\n"
                     : ACC32(C_IO, d) : "r"(a[0]), "r"(a[1]), "r"(a[2]), "r"(a[3]), "r"(lb), "n"(OB));
}
__host__ __device__ constexpr int koff(int kk, int chunk) { return ((kk >> 2) * chunk + (kk & 3) * 32) >> 4; }

__device__ __forceinline__ void stsm4(uint32_t addr, const uint4& v) {
    asm volatile("stmatrix.sync.aligned.m8n8.x4.shared.b16 [%0], {%1, %2, %3, %4};" ::"r"(addr), "r"(v.x), "r"(v.y), "r"(v.z), "r"(v.w) : "memory");
}
__device__ __forceinline__ void bulk_wait_read() { asm volatile("cp.async.bulk.wait_group.read 0;" ::: "memory"); }
template <int R> __device__ __forceinline__ void stage_round(const uint4 (&h)[12], uint32_t slot) {
    const uint32_t l = tid_now() & 31;
    const uint32_t sa = slot + (l & 7) * 128 + (((l >> 3) ^ (l & 7)) << 4);
#pragma unroll
    for (int i = 0; i < 2; i++) {
        const int r = (2 * R + i) / 3, c = (2 * R + i) % 3;
        stsm4(sa + i * 1024, h[4 * c + r]);
        stsm4((sa ^ 64) + i * 1024, h[4 * c + 2 + r]);
    }
}
__device__ __forceinline__ void stage_fence() {
    asm volatile("fence.proxy.async.shared::cta;" ::: "memory");
    __syncwarp();
}
template <int R> __device__ __forceinline__ void send_round(uint32_t slot, const CUtensorMap* tm, int col, int row) {
    asm volatile("{\n.reg .pred p;\nelect.sync _|p, 0xffffffff;\n"
                 "@p cp.async.bulk.tensor.4d.global.shared::cta.bulk_group [%0, {%2, %3, %4, %5}], [%1];\n"
                 "@p cp.async.bulk.commit_group;\n}\n"
                 ::"l"(tm + (R == 1)), "r"(slot), "r"(0), "r"(col), "r"(row + (R == 2)), "r"((int)(R == 2)) : "memory");
}
template <int R> __device__ __forceinline__ void store_round(const uint4 (&h)[12], uint32_t slot, const CUtensorMap* tm, int col, int row) {
    stage_round<R>(h, slot);
    stage_fence();
    send_round<R>(slot, tm, col, row);
}
__device__ __forceinline__ uint32_t warp4_uniform() { return __reduce_or_sync(0xffffffffu, (tid_now() >> 5) & 3); }
struct OutMaps { CUtensorMap m[2]; };
__host__ __device__ constexpr uint32_t bar_m(int c) { return kSmemBase + kOffBar + 32 + 8 * c; }
__device__ __forceinline__ void m_load(const Scratch* sc, int c, uint32_t par) {
    mbar_expect_tx(bar_m(c), 24576);
    bulk_load(kSmemBase + kOffWm + c * 24576, sc->img[par][0] + c * 1536, 24576, bar_m(c));
}
__device__ __forceinline__ bool m_agree(uint32_t ok) {
    uint32_t all;
    asm volatile("{\n.reg .pred p, q;\nsetp.ne.u32 p, %1, 0;\nbar.red.and.pred q, 7, 256, p;\nselp.b32 %0, 1, 0, q;\n}\n" : "=r"(all) : "r"(ok) : "memory");
    return all != 0;
}
__device__ __forceinline__ void m_check(const Scratch* sc, uint32_t par) {
    for (uint32_t round = 0;; round++) {
        uint32_t m = ~0u;
#pragma unroll 1
        for (int c = 0; c < 3; c++) {
            mbar_wait(bar_m(c), round & 1);
#pragma unroll
            for (int j = 0; j < 6; j++) {
                uint32_t v;
                asm volatile("ld.volatile.shared.b32 %0, [%1];" : "=r"(v)
                             : "r"(kSmemBase + kOffWm + c * 24576 + 4096 * j + (tid_now() & 127) * 32 + (tid_now() & 28)) : "memory");
                m = min(m, v);
            }
        }
        if (m_agree(m)) break;
        if (round > (1u << 20)) __trap();
        if (tid_now() == 128) {
            m_load(sc, 0, par); m_load(sc, 1, par); m_load(sc, 2, par);
        }
    }
}
constexpr uint32_t kBarV = kSmemBase + kOffBar + 56;
__device__ __forceinline__ void v_load(const Scratch* sc, uint32_t par) {
    mbar_expect_tx(kBarV, kWBytes);
#pragma unroll 1
    for (int c = 0; c < 3; c++) bulk_load(kSmemBase + kOffWv + c * 24576, sc->img[par][1] + c * 1536, 24576, kBarV);
}
__device__ __forceinline__ void v_check(const Scratch* sc, uint32_t par) {
    for (uint32_t round = 0;; round++) {
        mbar_wait(kBarV, round & 1);
        uint32_t m = ~0u;
#pragma unroll
        for (int j = 0; j < 18; j++) {
            uint32_t v;
            asm volatile("ld.volatile.shared.b32 %0, [%1];" : "=r"(v)
                         : "r"(kSmemBase + kOffWv + 4096 * j + (tid_now() & 127) * 32 + (tid_now() & 28)) : "memory");
            m = min(m, v);
        }
        uint32_t all;
        asm volatile("{\n.reg .pred p, q;\nsetp.ne.u32 p, %1, 0;\nbar.red.and.pred q, 14, 128, p;\nselp.b32 %0, 1, 0, q;\n}\n" : "=r"(all) : "r"(m) : "memory");
        if (all) break;
        if (round > (1u << 20)) __trap();
        if (tid_now() == 352) v_load(sc, par);
    }
}
template <int K> struct Gemm1 {
    static __device__ __forceinline__ void run(float (&d)[96], uint32_t lx, uint32_t lw, bool very_first, uint32_t st) {
        if constexpr (K > 0) Gemm1<K - 1>::run(d, lx, lw, very_first, st);
        if constexpr (K == 0 || K == 4 || K == 8) {
            if (very_first) mbar_wait(bar_m(K / 4), (st & kRound) != 0);
            wg_fence();
        }
        wg192_ss<K == 0, koff(K, 8192), koff(K, 24576)>(d, lx, lw);
    }
};
constexpr uint32_t kScAddr = kSmemBase + kOffBar + 96;
__device__ __forceinline__ void draw_ticket(uint32_t& ticket) {
    asm volatile("{\n.reg .pred p;\n.reg .b64 a;\nsetp.eq.u32 p, %1, 0;\nld.volatile.shared.u64 a, [%3];\n"
                 "@p atom.relaxed.gpu.global.inc.u32 %0, [a], %2;\n}\n"
                 : "+r"(ticket) : "r"(tid_now() & 127), "n"(kNWin - 1), "r"(kScAddr) : "memory");
}
#define G2_PASS 8
template <int KK> struct Gemm2 { static __device__ __forceinline__ void run(float (&d)[32], const uint32_t* a, uint32_t lx, uint32_t lnk, uint32_t& st) {
    Gemm2<KK - 1>::run(d, a, lx, lnk, st); wg64_rs<KK == 0, koff(KK, 8192)>(d, a + 4 * KK, lx);
    if constexpr (KK == G2_PASS) baton_pass(lnk, st); } };
template <> struct Gemm2<-1> { static __device__ __forceinline__ void run(float (&)[32], const uint32_t*, uint32_t, uint32_t, uint32_t&) {} };
template <int KK> struct Gemm3 { static __device__ __forceinline__ void run(float (&d)[96], const uint32_t* a, uint32_t lxt) {
    Gemm3<KK - 1>::run(d, a, lxt); wg192_rs<KK == 0, 1, KK * (2048 >> 4)>(d, a + 4 * KK, lxt); } };
template <> struct Gemm3<-1> { static __device__ __forceinline__ void run(float (&)[96], const uint32_t*, uint32_t) {} };
template <int K0, int KK> struct Gemm4 { static __device__ __forceinline__ void run(float (&d)[96], const uint32_t* a, uint32_t lw) {
    if constexpr (KK > K0) Gemm4<K0, KK - 1>::run(d, a, lw);
    wg192_rs<KK == 0, 0, koff(KK, 24576)>(d, a + 4 * KK, lw); } };

__device__ __forceinline__ uint32_t pack_bf16(float lo, float hi) {
    uint32_t r;
    asm("cvt.rn.bf16x2.f32 %0, %1, %2;" : "=r"(r) : "f"(hi), "f"(lo));
    return r;
}
__device__ __forceinline__ float ex2(float x) {
    float r;
    asm("ex2.approx.ftz.f32 %0, %1;" : "=f"(r) : "f"(x));
    return r;
}
__device__ __forceinline__ float rcp(float x) {
    float r;
    asm("rcp.approx.ftz.f32 %0, %1;" : "=f"(r) : "f"(x));
    return r;
}
__device__ __forceinline__ void mma16816(float (&c)[4], uint32_t a0, uint32_t a1, uint32_t a2, uint32_t a3,
                                         uint32_t b0, uint32_t b1) {
    asm volatile("mma.sync.aligned.m16n8k16.row.col.f32.bf16.bf16.f32 {%0,%1,%2,%3}, {%4,%5,%6,%7}, {%8,%9}, {%0,%1,%2,%3};"
                 : "+f"(c[0]), "+f"(c[1]), "+f"(c[2]), "+f"(c[3])
                 : "r"(a0), "r"(a1), "r"(a2), "r"(a3), "r"(b0), "r"(b1));
}

struct FoldRegs { uint4 B0[6], B1[6]; uint32_t A[48]; };

__device__ __forceinline__ void st_relaxed64(void* p, uint32_t a, uint32_t b, uint32_t on) {
    asm volatile("{\n.reg .pred q;\nsetp.ne.u32 q, %3, 0;\n@q st.relaxed.gpu.global.v2.b32 [%0], {%1, %2};\n}\n" ::"l"(p), "r"(a), "r"(b), "r"(on) : "memory");
}
__device__ __forceinline__ uint32_t pack_nonzero(float lo, float hi) { const uint32_t v = pack_bf16(lo, hi); return v != 0 ? v : 0x80000000u; }
__device__ __forceinline__ void fold_store(char* img, char* clear, uint32_t on, int n_lo, int n_hi, int k0, int q, const float (&c0)[4], const float (&c1)[4]) {
    const int u = ((k0 & 63) >> 3) + (q >> 1);
    const int base = (k0 >> 6) * 24576 + (q & 1) * 8;
    const int o_lo = base + n_lo * 128 + ((u ^ (n_lo & 7)) << 4), o_hi = base + n_hi * 128 + ((u ^ (n_hi & 7)) << 4);
    st_relaxed64(img + o_lo, pack_nonzero(c0[0], c0[1]), pack_nonzero(c1[0], c1[1]), on);
    st_relaxed64(img + o_hi, pack_nonzero(c0[2], c0[3]), pack_nonzero(c1[2], c1[3]), on);
    st_relaxed64(clear + o_lo, 0, 0, on);
    st_relaxed64(clear + o_hi, 0, 0, on);
}
__device__ __forceinline__ void fold_load_qk(FoldRegs& r, const __nv_bfloat16* __restrict__ wqkv, int tile, int lane) {
    const int g = lane >> 2, q = lane & 3;
    const int n0 = (tile / 12) * 16, k0 = (tile % 12) * 16;
    const int kb = k0 + 4 * (g >> 1) + (g & 1);
    const uint4* pa0 = reinterpret_cast<const uint4*>(wqkv + (size_t)(n0 + g) * 576 + 192 + 8 * q);
    const uint4* pa1 = reinterpret_cast<const uint4*>(wqkv + (size_t)(n0 + g + 8) * 576 + 192 + 8 * q);
    const uint4* pb0 = reinterpret_cast<const uint4*>(wqkv + (size_t)kb * 576 + 8 * q);
    const uint4* pb1 = reinterpret_cast<const uint4*>(wqkv + (size_t)(kb + 2) * 576 + 8 * q);
#pragma unroll
    for (int j = 0; j < 6; j++) {
        const uint4 lo = __ldg(pa0 + 4 * j), hi = __ldg(pa1 + 4 * j);
        r.A[8 * j + 0] = lo.x; r.A[8 * j + 1] = hi.x; r.A[8 * j + 2] = lo.y; r.A[8 * j + 3] = hi.y;
        r.A[8 * j + 4] = lo.z; r.A[8 * j + 5] = hi.z; r.A[8 * j + 6] = lo.w; r.A[8 * j + 7] = hi.w;
        r.B0[j] = __ldg(pb0 + 4 * j);
        r.B1[j] = __ldg(pb1 + 4 * j);
    }
}
__device__ __forceinline__ void fold_load_vo(FoldRegs& r, const __nv_bfloat16* __restrict__ wqkv, const __nv_bfloat16* __restrict__ wo,
                                             int tile, int lane) {
    const int g = lane >> 2, q = lane & 3;
    const int ch0 = (tile / 12) * 16 + 2 * g;
    const int k0 = (tile % 12) * 16;
    const int kb = k0 + 4 * (g >> 1) + (g & 1);
    const uint4* pb0 = reinterpret_cast<const uint4*>(wqkv + (size_t)kb * 576 + 384 + 8 * q);
    const uint4* pb1 = reinterpret_cast<const uint4*>(wqkv + (size_t)(kb + 2) * 576 + 384 + 8 * q);
    const uint32_t* pw = reinterpret_cast<const uint32_t*>(wo + (size_t)(8 * q) * kC + ch0);
#pragma unroll
    for (int j = 0; j < 6; j++) {
        r.B0[j] = __ldg(pb0 + 4 * j);
        r.B1[j] = __ldg(pb1 + 4 * j);
#pragma unroll
        for (int i = 0; i < 8; i++) r.A[8 * j + i] = __ldg(pw + (32 * j + i) * (kC / 2));
    }
}
template <bool kVO>
__device__ __forceinline__ void fold_compute_store(FoldRegs& r, Scratch* sc, int tile, int lane, uint32_t par, uint32_t on) {
    const int g = lane >> 2, q = lane & 3;
    float c0[4] = {0.f, 0.f, 0.f, 0.f}, c1[4] = {0.f, 0.f, 0.f, 0.f}, c2[4] = {0.f, 0.f, 0.f, 0.f}, c3[4] = {0.f, 0.f, 0.f, 0.f};
#pragma unroll
    for (int j = 0; j < 6; j++) {
        uint32_t a[8];
        if constexpr (kVO) {
#pragma unroll
            for (int i = 0; i < 4; i++) {
                a[2 * i]     = __byte_perm(r.A[8 * j + 2 * i], r.A[8 * j + 2 * i + 1], 0x5410);
                a[2 * i + 1] = __byte_perm(r.A[8 * j + 2 * i], r.A[8 * j + 2 * i + 1], 0x7632);
            }
        } else {
#pragma unroll
            for (int i = 0; i < 8; i++) a[i] = r.A[8 * j + i];
        }
        mma16816(c0, a[0], a[1], a[2], a[3], r.B0[j].x, r.B0[j].y);
        mma16816(c1, a[0], a[1], a[2], a[3], r.B1[j].x, r.B1[j].y);
        mma16816(c2, a[4], a[5], a[6], a[7], r.B0[j].z, r.B0[j].w);
        mma16816(c3, a[4], a[5], a[6], a[7], r.B1[j].z, r.B1[j].w);
    }
#pragma unroll
    for (int i = 0; i < 4; i++) { c0[i] += c2[i]; c1[i] += c3[i]; }
    const int k0 = (tile % 12) * 16;
    if constexpr (kVO) {
        const int n = (tile / 12) * 16 + 2 * g;
        fold_store(reinterpret_cast<char*>(sc->img[par][1]), reinterpret_cast<char*>(sc->img[par ^ 1][1]), on, n, n + 1, k0, q, c0, c1);
    } else {
        const int n0 = (tile / 12) * 16;
        fold_store(reinterpret_cast<char*>(sc->img[par][0]), reinterpret_cast<char*>(sc->img[par ^ 1][0]), on, n0 + g, n0 + g + 8, k0, q, c0, c1);
    }
}

__device__ __forceinline__ void prefetch_x(const CUtensorMap* tm, int win) {
    const int wh = win >> 6, ww = win & 63;
    asm volatile("cp.async.bulk.prefetch.tensor.3d.L2.global.tile [%0, {%1, %2, %3}];"
                 ::"l"(tm), "r"(0), "r"(ww * 8), "r"(wh * 8) : "memory");
}

__global__ void __launch_bounds__(kThreads, 1)
swin_attn_kernel(const __nv_bfloat16* __restrict__ wqkv, const __nv_bfloat16* __restrict__ wo, Scratch* __restrict__ sc,
                 const __grid_constant__ OutMaps tmo, const __grid_constant__ CUtensorMap tmx, const __grid_constant__ CUtensorMap tmp, const __grid_constant__ CUtensorMap tmc) {
    extern __shared__ uint8_t smem_raw[];
    constexpr uint32_t sbase = kSmemBase;
    if (smem_u32(smem_raw) != kSmemBase) __trap();
    const int tid = threadIdx.x, lane = tid & 31;
    const uint32_t warpu = __reduce_or_sync(0xffffffffu, (uint32_t)tid >> 5), wgu = warpu >> 2;
    const int warp = (int)warpu, wg = (int)wgu;
    const int G = gridDim.x;
    const uint32_t bar_full = sbase + kOffBar + 8 * wg;

    PROF(0); PROFG(1);
    if (wg == 0) FLOG(4096 + blockIdx.x * 4);
    const int ftile = blockIdx.x + (warp & 1) * G;
    FoldRegs fq;
#pragma unroll
    for (int j = 0; j < 6; j++) {
        asm volatile("" : "=r"(fq.B0[j].x), "=r"(fq.B0[j].y), "=r"(fq.B0[j].z), "=r"(fq.B0[j].w));
        asm volatile("" : "=r"(fq.B1[j].x), "=r"(fq.B1[j].y), "=r"(fq.B1[j].z), "=r"(fq.B1[j].w));
    }
#pragma unroll
    for (int j = 0; j < 48; j++) asm volatile("" : "=r"(fq.A[j]));
    if (warp < 2 && ftile < kTiles) fold_load_qk(fq, wqkv, ftile, lane);
    PSTAMP(0, 18);
    uint32_t epoch;
    asm volatile("ld.relaxed.gpu.global.u32 %0, [%1];" : "=r"(epoch) : "l"(sc->epoch) : "memory");
    if (warp == 10) {
        if (lane == 0) {
#pragma unroll
            for (int w = 0; w < kNWG; w++) mbar_init(sbase + kOffBar + 8 * w, 1);
            asm volatile("fence.mbarrier_init.release.cluster;" ::: "memory");
        }
        __syncwarp();
        asm volatile("bar.arrive 11, 384;" ::: "memory");
        if (lane == 0) {
            const uint32_t t0 = (uint32_t)clock64() + TRK_START + ((blockIdx.x * 37) & 63) * TRK_STAG / 64;
#pragma unroll
            for (int w = 0; w < kNWG; w++) mbar_expect_tx(sbase + kOffBar + 8 * w, kXBytes);
            PSTAMP(320, 18);
#pragma unroll 1
            for (int i = 0; i < 3 * kNWG + (PF_INIT > 0); i++) {
                while ((int)((uint32_t)clock64() - t0) < (i < 3 ? i * TRK_STEP0 : TRK_MID + (i - 3) * TRK_STEP)) {}
                const int w = i / 3, c = i % 3;
                if (w < kNWG) tma_load_x_chunk(sbase + kOffX + w * kXBytes + c * 8192, &tmc, sbase + kOffBar + 8 * w, w * G + blockIdx.x, c);
                else prefetch_x(&tmp, kNWG * G + blockIdx.x);
            }
        }
    }
    if (warp < 3) {
        for (int t = ftile;;) {
            const bool on = warp < 2 && t < kTiles;
            fold_compute_store<false>(fq, sc, t, lane, epoch & 1, on);
            if (lane == 0 && on) asm volatile("red.relaxed.gpu.global.add.u32 [%0], %1;" ::"l"(sc->cnt_m), "r"(1u) : "memory");
            PSTAMP(0, 20);
            t += 2 * G;
            if (__builtin_expect(warp == 2 || t >= kTiles, 1)) break;
            fold_load_qk(fq, wqkv, t, lane);
        }
    }
    if (warp < 4) {
        asm volatile("bar.sync 11, 384;" ::: "memory");
    } else if (warp == 4) {
        if (lane == 0) {
            set_link(0, 9); set_link(1, 8); set_link(2, 8);
            asm volatile("st.shared.u64 [%0], %1;" ::"r"(kScAddr), "l"(sc) : "memory");
            mbar_init(bar_m(0), 1);
            mbar_init(bar_m(1), 1);
            mbar_init(bar_m(2), 1);
            asm volatile("fence.mbarrier_init.release.cluster;" ::: "memory");
        }
        __syncwarp();
        asm volatile("bar.arrive 12, 128;" ::: "memory");
        asm volatile("bar.arrive 11, 384;" ::: "memory");
        if (lane == 0) {
            uint32_t v, spins = 0;
            do {
                asm volatile("ld.relaxed.gpu.global.u32 %0, [%1];" : "=r"(v) : "l"(sc->cnt_m) : "memory");
                if (++spins > (1u << 22)) __trap();
            } while (v < kTiles);
            PSTAMP(128, 21);
            const uint32_t par = epoch & 1;
            m_load(sc, 0, par); m_load(sc, 1, par); m_load(sc, 2, par);
            PSTAMP(128, 22);
        }
    } else if (warp == 11) {
        if (lane == 0) {
            mbar_init(kBarV, 1);
            asm volatile("fence.mbarrier_init.release.cluster;" ::: "memory");
        }
        __syncwarp();
        asm volatile("bar.sync 11, 384;" ::: "memory");
        if (lane == 0) {
            uint32_t v, spins = 0;
            do {
                asm volatile("ld.relaxed.gpu.global.u32 %0, [%1];" : "=r"(v) : "l"(sc->cnt_v) : "memory");
                if (++spins > (1u << 22)) __trap();
            } while (v < kTiles);
            PSTAMP(352, 23);
            { uint32_t ok = 0, n = 0;
              while (!ok && ++n < 64) asm volatile("{\n.reg .pred p;\nmbarrier.try_wait.parity.shared::cta.b64 p, [%1], 0;\nselp.b32 %0, 1, 0, p;\n}\n" : "=r"(ok) : "r"(bar_m(V_AFTER)) : "memory"); }
            v_load(sc, epoch & 1);
            PSTAMP(352, 24);
        }
    } else if (warp == 10) {
    } else if (warp >= 8) {
        asm volatile("bar.arrive 11, 384;" ::: "memory");
        { const uint32_t t0 = (uint32_t)clock64(); while ((uint32_t)clock64() - t0 < VO_DELAY) {} }
        FoldRegs fr;
        for (int t = G - 1 - blockIdx.x + (warp & 1) * G; t < kTiles; t += 2 * G) {
            fold_load_vo(fr, wqkv, wo, t, lane);
            fold_compute_store<true>(fr, sc, t, lane, epoch & 1, 1);
            PSTAMP(256, 18);
            if (lane == 0) asm volatile("red.relaxed.gpu.global.add.u32 [%0], %1;" ::"l"(sc->cnt_v), "r"(1u) : "memory");
            PSTAMP(256, 19);
        }
    } else {
        asm volatile("bar.arrive 11, 384;" ::: "memory");
        asm volatile("bar.sync 12, 128;" ::: "memory");
    }
    __syncwarp();
    if (wg == 1) m_check(sc, epoch & 1);
    uint4 hv[12];
#pragma unroll
    for (int a = 0; a < 12; a++) asm volatile("" : "=r"(hv[a].x), "=r"(hv[a].y), "=r"(hv[a].z), "=r"(hv[a].w));

    constexpr uint32_t dWm = ((sbase + kOffWm) >> 4) | (1u << 16);
    constexpr uint32_t dWv = ((sbase + kOffWv) >> 4) | (1u << 16);
    const float cs = 0.07216878364870322f * 1.4426950408889634f;
    PROF(2);
    PSTAMP(0, 23);
    PROF(3);
    if (wg == 2) {
        asm volatile("bar.sync 13, 128;" ::: "memory");
        v_check(sc, epoch & 1);
        PSTAMP(256, 23);
    }
    mbar_wait(bar_full, 0);
    PSTAMP(0, 24); PSTAMP(128, 24); PSTAMP(256, 24);

    uint32_t st = (uint32_t)(wg * G + blockIdx.x) << 17 | kFirst | (wg == 0 ? kSolo : 0);

    while (true) {
        float acc[96];
        uint32_t fa[48];
        const uint32_t dX = ((sbase + kOffX + wg_uniform() * kXBytes) >> 4) | (1u << 16);
        uint32_t ticket = 0;
        STAMP(0);
        uint32_t lnk = baton_wait(st, 0);
        STAMP(1);
        while (true) {
            const bool very_first = (st & kFirst) && tid_now() < 128;
            Gemm1<11>::run(acc, dX, dWm, very_first, st);
            wg_commit();
            if (!very_first) { baton_pass(lnk, st); break; }
            wg_wait0();
            if (m_agree(1)) break;
            st ^= kRound;
        }
        STAMP(2);
        if (!(st & kFirst)) {
            const uint32_t w4 = warp4_uniform();
            const uint32_t slot = sbase + kOffStage + w4 * 2048;
            const int col = (st_out(st) & 63) * 8, row = (st_out(st) >> 6) * 8 + 2 * w4;
            store_round<0>(hv, slot, tmo.m, col, row);
            bulk_wait_read(); __syncwarp();
            store_round<1>(hv, slot, tmo.m, col, row);
            bulk_wait_read(); __syncwarp();
            store_round<2>(hv, slot, tmo.m, col, row);
        }
        if ((st & kFirst) && (tid_now() == 128 || (PF_INIT > 2 && tid_now() == 256))) prefetch_x(&tmp, (kNWG + (tid_now() >> 7)) * gridDim.x + blockIdx.x);
        __syncwarp();
        draw_ticket(ticket);
        wg_wait0();
        STAMP(3);
        fence_regs(acc);
#pragma unroll
        for (int i = 0; i < 48; i++) fa[i] = pack_bf16(acc[2 * i], acc[2 * i + 1]);

        float s[32];
        fence_regs(fa);
        bulk_wait_read();
        STAMP(4);
        lnk = baton_wait(st, fa[47]);
        STAMP(5);
        wg_fence();
        Gemm2<11>::run(s, fa, dX, lnk, st);
        wg_commit();
        STAMP(6);
        wg_wait0();
        FLOG(st_win(st));
        STAMP(7);
        fence_regs(s);
        fence_regs(fa);

        uint32_t pa[16];
        {
            float a0[8], a1[8];
#pragma unroll
            for (int j = 0; j < 8; j++) { a0[j] = fmaxf(s[4 * j], s[4 * j + 1]); a1[j] = fmaxf(s[4 * j + 2], s[4 * j + 3]); }
#pragma unroll
            for (int d = 4; d > 0; d >>= 1)
#pragma unroll
                for (int j = 0; j < d; j++) { a0[j] = fmaxf(a0[j], a0[j + d]); a1[j] = fmaxf(a1[j], a1[j + d]); }
            float m0 = a0[0], m1 = a1[0];
            m0 = fmaxf(m0, __shfl_xor_sync(0xffffffffu, m0, 1));
            m1 = fmaxf(m1, __shfl_xor_sync(0xffffffffu, m1, 1));
            m0 = fmaxf(m0, __shfl_xor_sync(0xffffffffu, m0, 2));
            m1 = fmaxf(m1, __shfl_xor_sync(0xffffffffu, m1, 2));
            m0 *= cs; m1 *= cs;
            float l0 = 0.f, l1 = 0.f;
#pragma unroll
            for (int j = 0; j < 8; j++) {
                s[4 * j]     = ex2(fmaf(s[4 * j], cs, -m0));
                s[4 * j + 1] = ex2(fmaf(s[4 * j + 1], cs, -m0));
                s[4 * j + 2] = ex2(fmaf(s[4 * j + 2], cs, -m1));
                s[4 * j + 3] = ex2(fmaf(s[4 * j + 3], cs, -m1));
                l0 += s[4 * j] + s[4 * j + 1];
                l1 += s[4 * j + 2] + s[4 * j + 3];
            }
            l0 += __shfl_xor_sync(0xffffffffu, l0, 1);
            l1 += __shfl_xor_sync(0xffffffffu, l1, 1);
            l0 += __shfl_xor_sync(0xffffffffu, l0, 2);
            l1 += __shfl_xor_sync(0xffffffffu, l1, 2);
            const float r0 = rcp(l0), r1 = rcp(l1);
#pragma unroll
            for (int j = 0; j < 8; j++) {
                pa[2 * j]     = pack_bf16(s[4 * j] * r0, s[4 * j + 1] * r0);
                pa[2 * j + 1] = pack_bf16(s[4 * j + 2] * r1, s[4 * j + 3] * r1);
            }
        }

        fence_regs(pa);
        STAMP(8);
        lnk = baton_wait(st, pa[15]);
        if ((st & kFirst) && tid_now() == 0) set_link(1, 10);
        STAMP(9);
        wg_fence();
        Gemm3<3>::run(acc, pa, dX + (((8192u >> 4) - 1) << 16));
        wg_commit();
        baton_pass(lnk, st);
        STAMP(10);
        const int nxt = kNWG * (int)gridDim.x + (int)__reduce_or_sync(0xffffffffu, ticket);
        wg_wait0();
        STAMP(11);
        fence_regs(acc);
        fence_regs(pa);

        if (((tid_now() >> 5) & 3) == 0 && nxt < kNWin) {
            asm volatile("bar.sync %0, 128;" ::"r"((tid_now() >> 7) + 1) : "memory");
            if (elect_one()) {
                const uint32_t wgl = tid_now() >> 7;
                const uint32_t bar = sbase + kOffBar + 8 * wgl;
                mbar_expect_tx(bar, kXBytes);
                tma_load_x(sbase + kOffX + wgl * kXBytes, &tmx, bar, nxt);
            }
            __syncwarp();
        } else {
            asm volatile("bar.arrive %0, 128;" ::"r"((tid_now() >> 7) + 1) : "memory");
        }
#pragma unroll
        for (int i = 0; i < 48; i++) fa[i] = pack_bf16(acc[2 * i], acc[2 * i + 1]);

        asm volatile("st.volatile.shared.v4.b32 [%4], {%0, %1, %2, %3};"
                     :: "r"(fa[44]), "r"(fa[45]), "r"(fa[46]), "r"(fa[47]), "r"(sbase + kOffStash + (tid_now() & 127) * 16) : "memory");
        fence_regs(fa);
        STAMP(12);
        lnk = baton_wait(st, fa[43]);
        STAMP(13);
        if ((tid_now() & 127) == 0) {
            if (nxt >= kNWin) {
#pragma unroll
                for (int w = 0; w < kNWG; w++) {
                    uint32_t l;
                    asm volatile("ld.volatile.shared.u32 %0, [%1];" : "=r"(l) : "r"(kLink + 4 * w) : "memory");
                    if (l == (tid_now() >> 7) + 8) set_link(w, lnk);
                }
            }
            asm volatile("st.shared.u32 [%0], %1;" ::"r"(sbase + kOffBar + 64 + 4 * (tid_now() >> 7)), "r"(nxt) : "memory");
        }
        __syncwarp();
        wg_fence();
        Gemm4<0, 1>::run(acc, fa, dWv);
        wg_commit();
        Gemm4<2, 10>::run(acc, fa, dWv);
        wg_commit();
        wg_wait1();
        uint32_t fl[4];
        asm volatile("ld.volatile.shared.v4.b32 {%0, %1, %2, %3}, [%4];"
                     : "=r"(fl[0]), "=r"(fl[1]), "=r"(fl[2]), "=r"(fl[3]) : "r"(sbase + kOffStash + (tid_now() & 127) * 16) : "memory");
        wg_fence();
        wg192_rs<false, 0, koff(11, 24576)>(acc, fl, dWv);
        wg_commit();
        baton_pass(lnk, st);
        STAMP(14);
        if (((tid_now() >> 5) & 3) == 0) {
            asm volatile("bar.arrive %0, 128;" ::"r"((tid_now() >> 7) + 4) : "memory");
            if (elect_one()) {
                const int base = kNWG * (int)gridDim.x, t = nxt - base;
                auto lead = [&](int tt) { return min(min(PF_INIT * (int)gridDim.x + ((tt * PF_UP) >> 8), PF_LEAD), max(((kNWin - base - tt) * PF_DOWN) >> 8, PF_MIN)); };
                const int hi = base + t + lead(t);
                int lo = max(max(base + t - 1 + lead(t - 1), base + t) + 1, base + PF_INIT * (int)gridDim.x);
#pragma unroll 1
                for (; lo <= hi && lo < kNWin; lo++) prefetch_x(&tmp, lo);
                if (t == kNWin - 1) {
                    Scratch* q;
                    asm volatile("ld.volatile.shared.u64 %0, [%1];" : "=l"(q) : "r"(kScAddr) : "memory");
                    q->cnt_v[0] = 0; q->cnt_m[0] = 0; atomicAdd(q->epoch, 1);
                }
            }
            __syncwarp();
        } else {
            asm volatile("bar.sync %0, 128;" ::"r"((tid_now() >> 7) + 4) : "memory");
        }
        uint32_t pub;
        asm volatile("ld.shared.u32 %0, [%1];" : "=r"(pub) : "r"(sbase + kOffBar + 64 + 4 * (tid_now() >> 7)) : "memory");
        const int win_next = (int)__reduce_or_sync(0xffffffffu, pub);
        st = ((st ^ kPhase) & (kPhase | kSolo)) | st_win(st) << 4 | win_next << 17;
        if (win_next < kNWin) mbar_wait(sbase + kOffBar + 8 * (tid_now() >> 7), st & kPhase);
        wg_wait0();
        STAMP(15);
        fence_regs(acc);
        fence_regs(fa);
        fence_regs(fl);

        {
#pragma unroll
            for (int a = 0; a < 6; a++) {
                hv[2 * a].x     = pack_bf16(acc[16 * a + 0], acc[16 * a + 1]);
                hv[2 * a].y     = pack_bf16(acc[16 * a + 4], acc[16 * a + 5]);
                hv[2 * a].z     = pack_bf16(acc[16 * a + 8], acc[16 * a + 9]);
                hv[2 * a].w     = pack_bf16(acc[16 * a + 12], acc[16 * a + 13]);
                hv[2 * a + 1].x = pack_bf16(acc[16 * a + 2], acc[16 * a + 3]);
                hv[2 * a + 1].y = pack_bf16(acc[16 * a + 6], acc[16 * a + 7]);
                hv[2 * a + 1].z = pack_bf16(acc[16 * a + 10], acc[16 * a + 11]);
                hv[2 * a + 1].w = pack_bf16(acc[16 * a + 14], acc[16 * a + 15]);
            }
        }
        STAMP(16);
        if (win_next >= kNWin) break;
    }
    asm volatile("bar.sync %0, 128;" ::"r"((tid_now() >> 7) + 1) : "memory");
    {
        const uint32_t w4 = warp4_uniform();
        const uint32_t slot = sbase + kOffX + wg_uniform() * kXBytes + w4 * 6144;
        const int col = (st_out(st) & 63) * 8, row = (st_out(st) >> 6) * 8 + 2 * w4;
        stage_round<0>(hv, slot);
        stage_round<1>(hv, slot + 2048);
        stage_round<2>(hv, slot + 4096);
        stage_fence();
        send_round<0>(slot, tmo.m, col, row);
        send_round<1>(slot + 2048, tmo.m, col, row);
        send_round<2>(slot + 4096, tmo.m, col, row);
    }
    bulk_wait_read();
    FLOG(4096 + blockIdx.x * 4 + 1 + (tid_now() >> 7));
    PROF(4); PROFG(5);
    PROF_FLUSH();
}

typedef CUresult (*EncodeTiledFn)(CUtensorMap*, CUtensorMapDataType, cuuint32_t, void*, const cuuint64_t*,
                                  const cuuint64_t*, const cuuint32_t*, const cuuint32_t*, CUtensorMapInterleave,
                                  CUtensorMapSwizzle, CUtensorMapL2promotion, CUtensorMapFloatOOBfill);

}

extern "C" void kernel_launch(void* const* d_in, const int* in_sizes, int n_in, void* d_out, int out_size) {
    (void)in_sizes; (void)n_in; (void)out_size;
    const __nv_bfloat16* x    = (const __nv_bfloat16*)d_in[0];
    const __nv_bfloat16* wqkv = (const __nv_bfloat16*)d_in[1];
    const __nv_bfloat16* wo   = (const __nv_bfloat16*)d_in[2];

    static EncodeTiledFn encode = nullptr;
    static int num_sms = 0;
    static Scratch* scratch = nullptr;
    if (!encode) {
        void* fn = nullptr;
        cudaDriverEntryPointQueryResult qr;
        cudaGetDriverEntryPoint("cuTensorMapEncodeTiled", &fn, cudaEnableDefault, &qr);
        encode = (EncodeTiledFn)fn;
        cudaGetSymbolAddress((void**)&scratch, g_scratch);
        int dev = 0;
        cudaGetDevice(&dev);
        cudaDeviceGetAttribute(&num_sms, cudaDevAttrMultiProcessorCount, dev);
        cudaFuncSetAttribute(swin_attn_kernel, cudaFuncAttributeMaxDynamicSharedMemorySize, kSmemBytes);
    }
    CUtensorMap tmx;
    const cuuint64_t gdim[4] = {64, (cuuint64_t)kHW, (cuuint64_t)kHW, 3};
    const cuuint64_t gstr[3] = {(cuuint64_t)kC * 2, (cuuint64_t)kHW * kC * 2, 128};
    const cuuint32_t box[4] = {64, 8, 8, 3};
    const cuuint32_t estr[4] = {1, 1, 1, 1};
    encode(&tmx, CU_TENSOR_MAP_DATA_TYPE_BFLOAT16, 4, (void*)x, gdim, gstr, box, estr, CU_TENSOR_MAP_INTERLEAVE_NONE,
           CU_TENSOR_MAP_SWIZZLE_128B, CU_TENSOR_MAP_L2_PROMOTION_NONE, CU_TENSOR_MAP_FLOAT_OOB_FILL_NONE);

    CUtensorMap tmp;
    const cuuint64_t pdim[3] = {(cuuint64_t)kC, (cuuint64_t)kHW, (cuuint64_t)kHW};
    const cuuint64_t pstr[2] = {(cuuint64_t)kC * 2, (cuuint64_t)kHW * kC * 2};
    const cuuint32_t pbox[3] = {(cuuint32_t)kC, 8, 8};
    encode(&tmp, CU_TENSOR_MAP_DATA_TYPE_BFLOAT16, 3, (void*)x, pdim, pstr, pbox, estr, CU_TENSOR_MAP_INTERLEAVE_NONE,
           CU_TENSOR_MAP_SWIZZLE_NONE, CU_TENSOR_MAP_L2_PROMOTION_NONE, CU_TENSOR_MAP_FLOAT_OOB_FILL_NONE);
    CUtensorMap tmc;
    const cuuint32_t boxc[4] = {64, 8, 8, 1};
    encode(&tmc, CU_TENSOR_MAP_DATA_TYPE_BFLOAT16, 4, (void*)x, gdim, gstr, boxc, estr, CU_TENSOR_MAP_INTERLEAVE_NONE,
           CU_TENSOR_MAP_SWIZZLE_128B, CU_TENSOR_MAP_L2_PROMOTION_NONE, CU_TENSOR_MAP_FLOAT_OOB_FILL_NONE);
    OutMaps tmo;
    const cuuint32_t boxo[4] = {64, 8, 1, 2};
    encode(&tmo.m[0], CU_TENSOR_MAP_DATA_TYPE_BFLOAT16, 4, d_out, gdim, gstr, boxo, estr, CU_TENSOR_MAP_INTERLEAVE_NONE,
           CU_TENSOR_MAP_SWIZZLE_128B, CU_TENSOR_MAP_L2_PROMOTION_NONE, CU_TENSOR_MAP_FLOAT_OOB_FILL_NONE);
    const cuuint64_t odim[4] = {64, (cuuint64_t)kHW, (cuuint64_t)kHW, 2};
    const cuuint64_t ostr[3] = {(cuuint64_t)kC * 2, (cuuint64_t)kHW * kC * 2, (cuuint64_t)kHW * kC * 2 - 256};
    encode(&tmo.m[1], CU_TENSOR_MAP_DATA_TYPE_BFLOAT16, 4, (char*)d_out + 256, odim, ostr, boxo, estr, CU_TENSOR_MAP_INTERLEAVE_NONE,
           CU_TENSOR_MAP_SWIZZLE_128B, CU_TENSOR_MAP_L2_PROMOTION_NONE, CU_TENSOR_MAP_FLOAT_OOB_FILL_NONE);
    swin_attn_kernel<<<num_sms, kThreads, kSmemBytes, cudaStreamPerThread>>>(wqkv, wo, scratch, tmo, tmx, tmp, tmc);
}
```

```cpp
#include <cuda_runtime.h>
#include <cuda_bf16.h>
#include <cuda.h>
#include <stdint.h>

#define TICKET_AT 1
#define G4_PASS 11
namespace {

constexpr int kC      = 192;
constexpr int kHW     = 512;
#define MAXWIN 4096
constexpr int kNWin   = MAXWIN;
constexpr int kXBytes = 64 * kC * 2;
constexpr int kWBytes = kC * kC * 2;
constexpr int kNWG    = 3;
constexpr int kThreads = kNWG * 128;
constexpr int kTiles  = 144;
#define TRK_STEP 500
#define TRK_START 100
#define TRK_STAG 500
#define TRK_STEP0 750
#define TRK_MID 2400
#define PF_INIT 2
#define PF_LEAD 420
#define PF_UP 160
#define PF_DOWN 36
#define PF_MIN 200

constexpr int kOffWm  = 0;
constexpr int kOffWv  = kWBytes;
constexpr int kOffX   = 2 * kWBytes;
constexpr int kOffStage = kOffX + kNWG * kXBytes;
constexpr int kOffStash = kOffStage + 8192;
constexpr int kOffBar = kOffStash + 2048;
constexpr int kOffProf = kOffBar + 128;
constexpr int kSmemBytes = kOffProf;
constexpr uint32_t kSmemBase = 1024;

struct Scratch {
    uint32_t ticket[32];
    uint32_t epoch[32];
    uint32_t cnt_v[32];
    uint32_t cnt_m[32];
    uint4 img[2][2][kWBytes / 16];
};
__device__ __align__(128) Scratch g_scratch;

#define PROF(slot)
#define PROFG(slot)
#define PROFT(t, slot)
#define PROF_FLUSH()
#define STAMP(slot)
#define TSTAMP(slot)
#define PSTAMP(t, slot)
#define V_AFTER 2
#define VO_DELAY 700
#ifndef M_THR
#define M_THR 72
#endif
#define POLL_AT 0
#define VO_MODE 0
#define VO_COND (warp == 9)
#define FLOG(idx)
__device__ __forceinline__ uint32_t smem_u32(const void* p) { return (uint32_t)__cvta_generic_to_shared(p); }

__device__ __forceinline__ void mbar_init(uint32_t bar, uint32_t count) {
    asm volatile("mbarrier.init.shared::cta.b64 [%0], %1;" ::"r"(bar), "r"(count) : "memory");
}
__device__ __forceinline__ void mbar_expect_tx(uint32_t bar, uint32_t bytes) {
    asm volatile("mbarrier.arrive.expect_tx.shared::cta.b64 _, [%0], %1;" ::"r"(bar), "r"(bytes) : "memory");
}
__device__ __forceinline__ void mbar_wait(uint32_t bar, uint32_t parity) {
    uint32_t ok;
    uint32_t spins = 0;
    do {
        asm volatile("{\n.reg .pred p;\n"
                     "mbarrier.try_wait.parity.shared::cta.b64 p, [%1], %2;\n"
                     "selp.b32 %0, 1, 0, p;\n}\n"
                     : "=r"(ok) : "r"(bar), "r"(parity) : "memory");
        if (++spins > (1u << 26)) __trap();
    } while (!ok);
}
__device__ __forceinline__ uint32_t tid_now() {
    uint32_t t;
    asm volatile("mov.u32 %0, %%tid.x;" : "=r"(t));
    return t;
}
__device__ __forceinline__ bool elect_one() {
    uint32_t pred;
    asm volatile("{\n.reg .pred p;\nelect.sync _|p, 0xffffffff;\nselp.b32 %0, 1, 0, p;\n}\n" : "=r"(pred));
    return pred != 0;
}
__device__ __forceinline__ uint32_t wg_uniform() { return __reduce_or_sync(0xffffffffu, tid_now() >> 7); }
constexpr uint32_t kLink = kSmemBase + kOffBar + 64;
constexpr uint32_t kPhase = 1;
constexpr uint32_t kSolo = 2;
constexpr uint32_t kFirst = 4;
constexpr uint32_t kRound = 8;
__device__ __forceinline__ int st_out(uint32_t st) { return (st >> 4) & 0x1fff; }
__device__ __forceinline__ int st_win(uint32_t st) { return st >> 17; }
__device__ __forceinline__ uint32_t baton_wait(uint32_t st, uint32_t packed) {
    if (packed == 0xffffffffu) __trap();
    if (!(st & kSolo)) asm volatile("bar.sync %0, 256;" ::"r"((tid_now() >> 7) + 8) : "memory");
    uint32_t lnk;
    asm volatile("ld.volatile.shared.u32 %0, [%1];" : "=r"(lnk) : "r"(kLink + 8 * (tid_now() >> 7)) : "memory");
    return lnk;
}
__device__ __forceinline__ uint32_t baton_wait_pub(uint32_t st, uint32_t packed, uint32_t& pub) {
    if (packed == 0xffffffffu) __trap();
    asm volatile("bar.sync %0, %1;" ::"r"((tid_now() >> 7) + 8), "r"(st & kSolo ? 128 : 256) : "memory");
    uint32_t lnk;
    asm volatile("ld.volatile.shared.v2.u32 {%0, %1}, [%2];" : "=r"(lnk), "=r"(pub) : "r"(kLink + 8 * (tid_now() >> 7)) : "memory");
    return lnk;
}
__device__ __forceinline__ void baton_pass(uint32_t lnk, uint32_t& st) {
    const bool other = lnk != (tid_now() >> 7) + 8;
    if (other) asm volatile("bar.arrive %0, 256;" ::"r"(lnk) : "memory");
    st = other ? st & ~kSolo : st | kSolo;
}
__device__ __forceinline__ void set_link(int w, uint32_t v) { asm volatile("st.volatile.shared.u32 [%0], %1;" ::"r"(kLink + 8 * w), "r"(v) : "memory"); }
#define LD_EF_FROM 3100
constexpr uint64_t kPolNormal = 0x1000000000000000ull, kPolFirst = 0x12F0000000000000ull;
__device__ __forceinline__ void tma_load_x(uint32_t dst, const CUtensorMap* tm, uint32_t bar, int win) {
    const int wh = win >> 6, ww = win & 63;
    asm volatile("cp.async.bulk.tensor.4d.shared::cluster.global.mbarrier::complete_tx::bytes.L2::cache_hint"
                 " [%0], [%1, {%3, %4, %5, %6}], [%2], %7;"
                 ::"r"(dst), "l"(tm), "r"(bar), "r"(0), "r"(ww * 8), "r"(wh * 8), "r"(0), "l"(win >= LD_EF_FROM ? kPolFirst : kPolNormal) : "memory");
}
__device__ __forceinline__ void tma_load_x_chunk(uint32_t dst, const CUtensorMap* tm, uint32_t bar, int win, int chunk) {
    const int wh = win >> 6, ww = win & 63;
    asm volatile("cp.async.bulk.tensor.4d.shared::cluster.global.mbarrier::complete_tx::bytes"
                 " [%0], [%1, {%3, %4, %5, %6}], [%2];"
                 ::"r"(dst), "l"(tm), "r"(bar), "r"(0), "r"(ww * 8), "r"(wh * 8), "r"(chunk) : "memory");
}
__device__ __forceinline__ void bulk_load(uint32_t dst, const void* src, uint32_t bytes, uint32_t bar) {
    asm volatile("cp.async.bulk.shared::cluster.global.mbarrier::complete_tx::bytes [%0], [%1], %2, [%3];"
                 ::"r"(dst), "l"(src), "r"(bytes), "r"(bar) : "memory");
}

__device__ __forceinline__ void wg_fence()  { asm volatile("wgmma.fence.sync.aligned;" ::: "memory"); }
__device__ __forceinline__ void wg_commit() { asm volatile("wgmma.commit_group.sync.aligned;" ::: "memory"); }
__device__ __forceinline__ void wg_wait0()  { asm volatile("wgmma.wait_group.sync.aligned 0;" ::: "memory"); }
__device__ __forceinline__ void wg_wait1()  { asm volatile("wgmma.wait_group.sync.aligned 1;" ::: "memory"); }
__device__ __forceinline__ void wg_wait2()  { asm volatile("wgmma.wait_group.sync.aligned 2;" ::: "memory"); }

template <int N> __device__ __forceinline__ void fence_regs(float (&d)[N]) {
#pragma unroll
    for (int i = 0; i < N; i++) asm volatile("" : "+f"(d[i])::"memory");
}
template <int N> __device__ __forceinline__ void fence_regs(uint32_t (&d)[N]) {
#pragma unroll
    for (int i = 0; i < N; i++) asm volatile("" : "+r"(d[i])::"memory");
}

#define ACC8(c, d, i) c(d[i]), c(d[i + 1]), c(d[i + 2]), c(d[i + 3]), c(d[i + 4]), c(d[i + 5]), c(d[i + 6]), c(d[i + 7])
#define ACC32(c, d) ACC8(c, d, 0), ACC8(c, d, 8), ACC8(c, d, 16), ACC8(c, d, 24)
#define ACC96(c, d) ACC32(c, d), ACC8(c, d, 32), ACC8(c, d, 40), ACC8(c, d, 48), ACC8(c, d, 56), \
                    ACC8(c, d, 64), ACC8(c, d, 72), ACC8(c, d, 80), ACC8(c, d, 88)
#define C_IO(x) "+f"(x)
#define C_O(x) "=f"(x)
#define REGS32 "{%0, %1, %2, %3, %4, %5, %6, %7, %8, %9, %10, %11, %12, %13, %14, %15, " \
               "%16, %17, %18, %19, %20, %21, %22, %23, %24, %25, %26, %27, %28, %29, %30, %31}"
#define REGS96 "{%0, %1, %2, %3, %4, %5, %6, %7, %8, %9, %10, %11, %12, %13, %14, %15, " \
               "%16, %17, %18, %19, %20, %21, %22, %23, %24, %25, %26, %27, %28, %29, %30, %31, " \
               "%32, %33, %34, %35, %36, %37, %38, %39, %40, %41, %42, %43, %44, %45, %46, %47, " \
               "%48, %49, %50, %51, %52, %53, %54, %55, %56, %57, %58, %59, %60, %61, %62, %63, " \
               "%64, %65, %66, %67, %68, %69, %70, %71, %72, %73, %74, %75, %76, %77, %78, %79, " \
               "%80, %81, %82, %83, %84, %85, %86, %87, %88, %89, %90, %91, %92, %93, %94, %95}"

#define DESC_HI "0x40000040"
#define MK_DESC(name, lo, off) "add.u32 t, " lo ", " off ";\nmov.b64 " name ", {t, " DESC_HI "};\n"

template <bool First, int OA, int OB> __device__ __forceinline__ void wg192_ss(float (&d)[96], uint32_t la, uint32_t lb) {
    if constexpr (First)
        asm volatile("{\n.reg .pred p;\n.reg .b32 t;\n.reg .b64 da, db;\nsetp.ne.b32 p, 0, 0;\n"
                     MK_DESC("da", "%96", "%98") MK_DESC("db", "%97", "%99")
                     "wgmma.mma_async.sync.aligned.m64n192k16.f32.bf16.bf16 " REGS96 ", da, db, p, 1, 1, 0, 0;\n}\n"
                     : ACC96(C_O, d) : "r"(la), "r"(lb), "n"(OA), "n"(OB));
    else
        asm volatile("{\n.reg .pred p;\n.reg .b32 t;\n.reg .b64 da, db;\nsetp.ne.b32 p, 1, 0;\n"
                     MK_DESC("da", "%96", "%98") MK_DESC("db", "%97", "%99")
                     "wgmma.mma_async.sync.aligned.m64n192k16.f32.bf16.bf16 " REGS96 ", da, db, p, 1, 1, 0, 0;\n}\n"
                     : ACC96(C_IO, d) : "r"(la), "r"(lb), "n"(OA), "n"(OB));
}
template <bool First, int TB, int OB> __device__ __forceinline__ void wg192_rs(float (&d)[96], const uint32_t* a, uint32_t lb) {
    if constexpr (First)
        asm volatile("{\n.reg .pred p;\n.reg .b32 t;\n.reg .b64 db;\nsetp.ne.b32 p, 0, 0;\n"
                     MK_DESC("db", "%100", "%102")
                     "wgmma.mma_async.sync.aligned.m64n192k16.f32.bf16.bf16 " REGS96 ", {%96, %97, %98, %99}, db, p, 1, 1, %101;\n}\n"
                     : ACC96(C_O, d) : "r"(a[0]), "r"(a[1]), "r"(a[2]), "r"(a[3]), "r"(lb), "n"(TB), "n"(OB));
    else
        asm volatile("{\n.reg .pred p;\n.reg .b32 t;\n.reg .b64 db;\nsetp.ne.b32 p, 1, 0;\n"
                     MK_DESC("db", "%100", "%102")
                     "wgmma.mma_async.sync.aligned.m64n192k16.f32.bf16.bf16 " REGS96 ", {%96, %97, %98, %99}, db, p, 1, 1, %101;\n}\n"
                     : ACC96(C_IO, d) : "r"(a[0]), "r"(a[1]), "r"(a[2]), "r"(a[3]), "r"(lb), "n"(TB), "n"(OB));
}
template <bool First, int TB, int OB> __device__ __forceinline__ void wg64_rs(float (&d)[32], const uint32_t* a, uint32_t lb) {
    if constexpr (First)
        asm volatile("{\n.reg .pred p;\n.reg .b32 t;\n.reg .b64 db;\nsetp.ne.b32 p, 0, 0;\n"
                     MK_DESC("db", "%36", "%38")
                     "wgmma.mma_async.sync.aligned.m64n64k16.f32.bf16.bf16 " REGS32 ", {%32, %33, %34, %35}, db, p, 1, 1, %37;\n}\n"
                     : ACC32(C_O, d) : "r"(a[0]), "r"(a[1]), "r"(a[2]), "r"(a[3]), "r"(lb), "n"(TB), "n"(OB));
    else
        asm volatile("{\n.reg .pred p;\n.reg .b32 t;\n.reg .b64 db;\nsetp.ne.b32 p, 1, 0;\n"
                     MK_DESC("db", "%36", "%38")
                     "wgmma.mma_async.sync.aligned.m64n64k16.f32.bf16.bf16 " REGS32 ", {%32, %33, %34, %35}, db, p, 1, 1, %37;\n}\n"
                     : ACC32(C_IO, d) : "r"(a[0]), "r"(a[1]), "r"(a[2]), "r"(a[3]), "r"(lb), "n"(TB), "n"(OB));
}
#define HI_OP "n"(0x40000040)
template <int Acc, int TB, int OB> __device__ __forceinline__ void wg64_last(float (&d)[32], const uint32_t* a, uint32_t lb, uint32_t hi, uint32_t one) {
    if constexpr (Acc == 0)
        asm volatile("{\n.reg .pred p;\n.reg .b32 t;\n.reg .b64 db;\nsetp.ne.b32 p, 0, 0;\nadd.u32 t, %36, %38;\nmov.b64 db, {t, %39};\n"
                     "wgmma.mma_async.sync.aligned.m64n64k16.f32.bf16.bf16 " REGS32 ", {%32, %33, %34, %35}, db, p, 1, 1, %37;\n}\n"
                     : ACC32(C_O, d) : "r"(a[0]), "r"(a[1]), "r"(a[2]), "r"(a[3]), "r"(lb), "n"(TB), "n"(OB), HI_OP);
    else if constexpr (Acc == 1)
        asm volatile("{\n.reg .pred p;\n.reg .b32 t;\n.reg .b64 db;\nsetp.ne.b32 p, 1, 0;\nadd.u32 t, %36, %38;\nmov.b64 db, {t, %39};\n"
                     "wgmma.mma_async.sync.aligned.m64n64k16.f32.bf16.bf16 " REGS32 ", {%32, %33, %34, %35}, db, p, 1, 1, %37;\n}\n"
                     : ACC32(C_IO, d) : "r"(a[0]), "r"(a[1]), "r"(a[2]), "r"(a[3]), "r"(lb), "n"(TB), "n"(OB), HI_OP);
    else
        asm volatile("{\n.reg .pred p;\n.reg .b32 t;\n.reg .b64 db;\nsetp.ne.b32 p, %40, 1;\nadd.u32 t, %36, %38;\nmov.b64 db, {t, %39};\n"
                     "wgmma.mma_async.sync.aligned.m64n64k16.f32.bf16.bf16 " REGS32 ", {%32, %33, %34, %35}, db, p, 1, 1, %37;\n}\n"
                     : ACC32(C_IO, d) : "r"(a[0]), "r"(a[1]), "r"(a[2]), "r"(a[3]), "r"(lb), "n"(TB), "n"(OB), HI_OP, "r"(one));
}
__host__ __device__ constexpr int koff(int kk, int chunk) { return ((kk >> 2) * chunk + (kk & 3) * 32) >> 4; }

__device__ __forceinline__ void stsm4(uint32_t addr, const uint4& v) {
    asm volatile("stmatrix.sync.aligned.m8n8.x4.shared.b16 [%0], {%1, %2, %3, %4};" ::"r"(addr), "r"(v.x), "r"(v.y), "r"(v.z), "r"(v.w) : "memory");
}
__device__ __forceinline__ void bulk_wait_read() {
    asm volatile("cp.async.bulk.wait_group.read 0;" ::: "memory");
}
__device__ __forceinline__ uint32_t stage_addr(uint32_t slot, uint32_t l) { return slot + (l & 7) * 128 + ((((l >> 3) & 3) ^ (l & 7)) << 4); }
__device__ __forceinline__ uint32_t tid_opaque() { return __shfl_sync(0xffffffffu, tid_now(), tid_now() & 31); }
template <int R> __device__ __forceinline__ void stage_round(const uint4 (&h)[12], uint32_t sa) {
#pragma unroll
    for (int i = 0; i < 2; i++) {
        const int r = (2 * R + i) / 3, c = (2 * R + i) % 3;
        stsm4(sa + i * 1024, h[4 * c + r]);
        stsm4((sa ^ 64) + i * 1024, h[4 * c + 2 + r]);
    }
}
__device__ __forceinline__ void stage_fence() {
    asm volatile("fence.proxy.async.shared::cta;" ::: "memory");
    __syncwarp();
}
template <int R> __device__ __forceinline__ void send_round(uint32_t slot, const CUtensorMap* tm, int col, int row) {
    asm volatile("{\n.reg .pred p;\nelect.sync _|p, 0xffffffff;\n"
                 "@p cp.async.bulk.tensor.4d.global.shared::cta.bulk_group [%0, {%2, %3, %4, %5}], [%1];\n"
                 "@p cp.async.bulk.commit_group;\n}\n"
                 ::"l"(tm + (R == 1)), "r"(slot), "r"(0), "r"(col), "r"(row + (R == 2)), "r"((int)(R == 2)) : "memory");
}
template <int R> __device__ __forceinline__ void store_round(const uint4 (&h)[12], uint32_t slot, const CUtensorMap* tm, int col, int row) {
    stage_round<R>(h, stage_addr(slot, tid_now()));
    stage_fence();
    send_round<R>(slot, tm, col, row);
}
__device__ __forceinline__ uint32_t warp4_uniform() { return __reduce_or_sync(0xffffffffu, (tid_now() >> 5) & 3); }
struct OutMaps { CUtensorMap m[2]; };
__host__ __device__ constexpr uint32_t bar_m(int c) { return kSmemBase + kOffBar + 32 + 8 * c; }
__device__ __forceinline__ void m_load(const Scratch* sc, int c, uint32_t par) {
    mbar_expect_tx(bar_m(c), 24576);
    bulk_load(kSmemBase + kOffWm + c * 24576, sc->img[par][0] + c * 1536, 24576, bar_m(c));
}
__device__ __forceinline__ bool m_agree(uint32_t ok) {
    uint32_t all;
    asm volatile("{\n.reg .pred p, q;\nsetp.ne.u32 p, %1, 0;\nbar.red.and.pred q, 7, 256, p;\nselp.b32 %0, 1, 0, q;\n}\n" : "=r"(all) : "r"(ok) : "memory");
    return all != 0;
}
__device__ __forceinline__ void m_check(const Scratch* sc, uint32_t par) {
    for (uint32_t round = 0;; round++) {
        uint32_t m = ~0u;
#pragma unroll 1
        for (int c = 0; c < 3; c++) {
            mbar_wait(bar_m(c), round & 1);
#pragma unroll
            for (int j = 0; j < 6; j++) {
                uint32_t v;
                asm volatile("ld.volatile.shared.b32 %0, [%1];" : "=r"(v)
                             : "r"(kSmemBase + kOffWm + c * 24576 + 4096 * j + (tid_now() & 127) * 32 + (tid_now() & 28)) : "memory");
                m = min(m, v);
            }
        }
        if (m_agree(m)) break;
        if (round > (1u << 20)) __trap();
        if (tid_now() == 128) {
            m_load(sc, 0, par); m_load(sc, 1, par); m_load(sc, 2, par);
        }
    }
}
constexpr uint32_t kBarV = kSmemBase + kOffBar + 56;
__device__ __forceinline__ void v_load(const Scratch* sc, uint32_t par) {
    mbar_expect_tx(kBarV, kWBytes);
#pragma unroll 1
    for (int c = 0; c < 3; c++) bulk_load(kSmemBase + kOffWv + c * 24576, sc->img[par][1] + c * 1536, 24576, kBarV);
}
__device__ __forceinline__ void v_check(const Scratch* sc, uint32_t par) {
    for (uint32_t round = 0;; round++) {
        mbar_wait(kBarV, round & 1);
        uint32_t m = ~0u;
#pragma unroll
        for (int j = 0; j < 18; j++) {
            uint32_t v;
            asm volatile("ld.volatile.shared.b32 %0, [%1];" : "=r"(v)
                         : "r"(kSmemBase + kOffWv + 4096 * j + (tid_now() & 127) * 32 + (tid_now() & 28)) : "memory");
            m = min(m, v);
        }
        uint32_t all;
        asm volatile("{\n.reg .pred p, q;\nsetp.ne.u32 p, %1, 0;\nbar.red.and.pred q, 14, 128, p;\nselp.b32 %0, 1, 0, q;\n}\n" : "=r"(all) : "r"(m) : "memory");
        if (all) break;
        if (round > (1u << 20)) __trap();
        if (tid_now() == 352) v_load(sc, par);
    }
}
template <int K> struct Gemm1 {
    static __device__ __forceinline__ void run(float (&d)[96], uint32_t lx, uint32_t lw, bool very_first, uint32_t st) {
        if constexpr (K > 0) Gemm1<K - 1>::run(d, lx, lw, very_first, st);
        if constexpr (K == 0 || K == 4 || K == 8) {
            if (very_first) mbar_wait(bar_m(K / 4), (st & kRound) != 0);
            wg_fence();
        }
        wg192_ss<K == 0, koff(K, 8192), koff(K, 24576)>(d, lx, lw);
    }
};
constexpr uint32_t kScAddr = kSmemBase + kOffBar + 96;
__device__ __forceinline__ void draw_ticket(uint32_t& ticket) {
    asm volatile("{\n.reg .pred p;\n.reg .b64 a;\nsetp.eq.u32 p, %1, 0;\nld.volatile.shared.u64 a, [%3];\n"
                 "@p atom.relaxed.gpu.global.inc.u32 %0, [a], %2;\n}\n"
                 : "+r"(ticket) : "r"(tid_now() & 127), "n"(kNWin - 1), "r"(kScAddr) : "memory");
}
#define ALONE_COND (lnk == (tid_now() >> 7) + 8 && pub >= kNWin)
#define ALONE_V 4
#define G2_PASS 9
template <int KK> struct Gemm2 { static __device__ __forceinline__ void run(float (&d)[32], const uint32_t* a, uint32_t lx, uint32_t lnk, uint32_t& st) {
    Gemm2<KK - 1>::run(d, a, lx, lnk, st); wg64_rs<KK == 0, 0, koff(KK, 8192)>(d, a + 4 * KK, lx);
    if constexpr (KK == G2_PASS) baton_pass(lnk, st); } };
template <> struct Gemm2<-1> { static __device__ __forceinline__ void run(float (&)[32], const uint32_t*, uint32_t, uint32_t, uint32_t&) {} };
template <int KK> struct Gemm3 { static __device__ __forceinline__ void run(float (&d)[96], const uint32_t* a, uint32_t lxt) {
    Gemm3<KK - 1>::run(d, a, lxt); wg192_rs<KK == 0, 1, KK * (2048 >> 4)>(d, a + 4 * KK, lxt); } };
template <> struct Gemm3<-1> { static __device__ __forceinline__ void run(float (&)[96], const uint32_t*, uint32_t) {} };
template <int K0, int KK> struct Gemm4 { static __device__ __forceinline__ void run(float (&d)[96], const uint32_t* a, uint32_t lw) {
    if constexpr (KK > K0) Gemm4<K0, KK - 1>::run(d, a, lw);
    wg192_rs<KK == 0, 0, koff(KK, 24576)>(d, a + 4 * KK, lw); } };

template <int C, int KK> struct Gemm3s { static __device__ __forceinline__ void run(float (&d)[32], const uint32_t* a, uint32_t lxt, uint32_t one) {
    if constexpr (KK > 0) Gemm3s<C, KK - 1>::run(d, a, lxt, one);
    wg64_last<KK != 0, 1, (C * 8192 + KK * 2048) / 16>(d, a + 4 * KK, lxt, one * 0x40000040u, one); } };
template <int C, int K0, int KK> struct Gemm4s { static __device__ __forceinline__ void run(float (&d)[32], const uint32_t* a, uint32_t lw, uint32_t one) {
    if constexpr (KK > K0) Gemm4s<C, K0, KK - 1>::run(d, a, lw, one);
    wg64_last<KK == 0 ? 2 : 1, 0, koff(KK, 24576) + C * 8192 / 16>(d, a + 4 * KK, lw, one * 0x40000040u, one); } };

__device__ __forceinline__ uint32_t pack_bf16(float lo, float hi) {
    uint32_t r;
    asm("cvt.rn.bf16x2.f32 %0, %1, %2;" : "=r"(r) : "f"(hi), "f"(lo));
    return r;
}
__device__ __forceinline__ float ex2(float x) {
    float r;
    asm("ex2.approx.ftz.f32 %0, %1;" : "=f"(r) : "f"(x));
    return r;
}
__device__ __forceinline__ float rcp(float x) {
    float r;
    asm("rcp.approx.ftz.f32 %0, %1;" : "=f"(r) : "f"(x));
    return r;
}
__device__ __forceinline__ void mma16816(float (&c)[4], uint32_t a0, uint32_t a1, uint32_t a2, uint32_t a3,
                                         uint32_t b0, uint32_t b1) {
    asm volatile("mma.sync.aligned.m16n8k16.row.col.f32.bf16.bf16.f32 {%0,%1,%2,%3}, {%4,%5,%6,%7}, {%8,%9}, {%0,%1,%2,%3};"
                 : "+f"(c[0]), "+f"(c[1]), "+f"(c[2]), "+f"(c[3])
                 : "r"(a0), "r"(a1), "r"(a2), "r"(a3), "r"(b0), "r"(b1));
}

struct FoldRegs { uint4 B0[6], B1[6]; uint32_t A[48]; };

__device__ __forceinline__ void st_relaxed64(void* p, uint32_t a, uint32_t b, uint32_t on) {
    asm volatile("{\n.reg .pred q;\nsetp.ne.u32 q, %3, 0;\n@q st.relaxed.gpu.global.v2.b32 [%0], {%1, %2};\n}\n" ::"l"(p), "r"(a), "r"(b), "r"(on) : "memory");
}
__device__ __forceinline__ uint32_t pack_nonzero(float lo, float hi) { const uint32_t v = pack_bf16(lo, hi); return v != 0 ? v : 0x80000000u; }
__device__ __forceinline__ void fold_store(char* img, char* clear, uint32_t on, int n_lo, int n_hi, int k0, int q, const float (&c0)[4], const float (&c1)[4]) {
    const int u = ((k0 & 63) >> 3) + (q >> 1);
    const int base = (k0 >> 6) * 24576 + (q & 1) * 8;
    const int o_lo = base + n_lo * 128 + ((u ^ (n_lo & 7)) << 4), o_hi = base + n_hi * 128 + ((u ^ (n_hi & 7)) << 4);
    st_relaxed64(img + o_lo, pack_nonzero(c0[0], c0[1]), pack_nonzero(c1[0], c1[1]), on);
    st_relaxed64(img + o_hi, pack_nonzero(c0[2], c0[3]), pack_nonzero(c1[2], c1[3]), on);
    st_relaxed64(clear + o_lo, 0, 0, on);
    st_relaxed64(clear + o_hi, 0, 0, on);
}
__device__ __forceinline__ void fold_load_qk(FoldRegs& r, const __nv_bfloat16* __restrict__ wqkv, int tile, int lane) {
    const int g = lane >> 2, q = lane & 3;
    const int n0 = (tile / 12) * 16, k0 = (tile % 12) * 16;
    const int kb = k0 + 4 * (g >> 1) + (g & 1);
    const uint4* pa0 = reinterpret_cast<const uint4*>(wqkv + (size_t)(n0 + g) * 576 + 192 + 8 * q);
    const uint4* pa1 = reinterpret_cast<const uint4*>(wqkv + (size_t)(n0 + g + 8) * 576 + 192 + 8 * q);
    const uint4* pb0 = reinterpret_cast<const uint4*>(wqkv + (size_t)kb * 576 + 8 * q);
    const uint4* pb1 = reinterpret_cast<const uint4*>(wqkv + (size_t)(kb + 2) * 576 + 8 * q);
#pragma unroll
    for (int j = 0; j < 6; j++) {
        const uint4 lo = __ldg(pa0 + 4 * j), hi = __ldg(pa1 + 4 * j);
        r.A[8 * j + 0] = lo.x; r.A[8 * j + 1] = hi.x; r.A[8 * j + 2] = lo.y; r.A[8 * j + 3] = hi.y;
        r.A[8 * j + 4] = lo.z; r.A[8 * j + 5] = hi.z; r.A[8 * j + 6] = lo.w; r.A[8 * j + 7] = hi.w;
        r.B0[j] = __ldg(pb0 + 4 * j);
        r.B1[j] = __ldg(pb1 + 4 * j);
    }
}
__device__ __forceinline__ void fold_load_vo(FoldRegs& r, const __nv_bfloat16* __restrict__ wqkv, const __nv_bfloat16* __restrict__ wo,
                                             int tile, int lane) {
    const int g = lane >> 2, q = lane & 3;
    const int ch0 = (tile / 12) * 16 + 2 * g;
    const int k0 = (tile % 12) * 16;
    const int kb = k0 + 4 * (g >> 1) + (g & 1);
    const uint4* pb0 = reinterpret_cast<const uint4*>(wqkv + (size_t)kb * 576 + 384 + 8 * q);
    const uint4* pb1 = reinterpret_cast<const uint4*>(wqkv + (size_t)(kb + 2) * 576 + 384 + 8 * q);
    const uint32_t* pw = reinterpret_cast<const uint32_t*>(wo + (size_t)(8 * q) * kC + ch0);
#pragma unroll
    for (int j = 0; j < 6; j++) {
        r.B0[j] = __ldg(pb0 + 4 * j);
        r.B1[j] = __ldg(pb1 + 4 * j);
#pragma unroll
        for (int i = 0; i < 8; i++) r.A[8 * j + i] = __ldg(pw + (32 * j + i) * (kC / 2));
    }
}
template <bool kVO>
__device__ __forceinline__ void fold_compute_store(FoldRegs& r, Scratch* sc, int tile, int lane, uint32_t par, uint32_t on) {
    const int g = lane >> 2, q = lane & 3;
    float c0[4] = {0.f, 0.f, 0.f, 0.f}, c1[4] = {0.f, 0.f, 0.f, 0.f}, c2[4] = {0.f, 0.f, 0.f, 0.f}, c3[4] = {0.f, 0.f, 0.f, 0.f};
#pragma unroll
    for (int j = 0; j < 6; j++) {
        uint32_t a[8];
        if constexpr (kVO) {
#pragma unroll
            for (int i = 0; i < 4; i++) {
                a[2 * i]     = __byte_perm(r.A[8 * j + 2 * i], r.A[8 * j + 2 * i + 1], 0x5410);
                a[2 * i + 1] = __byte_perm(r.A[8 * j + 2 * i], r.A[8 * j + 2 * i + 1], 0x7632);
            }
        } else {
#pragma unroll
            for (int i = 0; i < 8; i++) a[i] = r.A[8 * j + i];
        }
        mma16816(c0, a[0], a[1], a[2], a[3], r.B0[j].x, r.B0[j].y);
        mma16816(c1, a[0], a[1], a[2], a[3], r.B1[j].x, r.B1[j].y);
        mma16816(c2, a[4], a[5], a[6], a[7], r.B0[j].z, r.B0[j].w);
        mma16816(c3, a[4], a[5], a[6], a[7], r.B1[j].z, r.B1[j].w);
    }
#pragma unroll
    for (int i = 0; i < 4; i++) { c0[i] += c2[i]; c1[i] += c3[i]; }
    const int k0 = (tile % 12) * 16;
    if constexpr (kVO) {
        const int n = (tile / 12) * 16 + 2 * g;
        fold_store(reinterpret_cast<char*>(sc->img[par][1]), reinterpret_cast<char*>(sc->img[par ^ 1][1]), on, n, n + 1, k0, q, c0, c1);
    } else {
        const int n0 = (tile / 12) * 16;
        fold_store(reinterpret_cast<char*>(sc->img[par][0]), reinterpret_cast<char*>(sc->img[par ^ 1][0]), on, n0 + g, n0 + g + 8, k0, q, c0, c1);
    }
}

__device__ __forceinline__ void prefetch_x(const CUtensorMap* tm, int win) {
    const int wh = win >> 6, ww = win & 63;
    asm volatile("cp.async.bulk.prefetch.tensor.3d.L2.global.tile [%0, {%1, %2, %3}];"
                 ::"l"(tm), "r"(0), "r"(ww * 8), "r"(wh * 8) : "memory");
}

__device__ __forceinline__ void reset_for_next_launch() {
    Scratch* q;
    asm volatile("ld.volatile.shared.u64 %0, [%1];" : "=l"(q) : "r"(kScAddr) : "memory");
    q->cnt_v[0] = 0; q->cnt_m[0] = 0; atomicAdd(q->epoch, 1);
}
__device__ __forceinline__ void finish_alone(uint32_t dXt, uint32_t dWv, [[maybe_unused]] const CUtensorMap* tm, int win) {
    uint32_t pa[16];
#pragma unroll
    for (int j = 0; j < 4; j++)
        asm volatile("ld.volatile.shared.v4.b32 {%0, %1, %2, %3}, [%4];" : "=r"(pa[4 * j]), "=r"(pa[4 * j + 1]), "=r"(pa[4 * j + 2]), "=r"(pa[4 * j + 3])
                     : "r"(kSmemBase + kOffStage + j * 2048 + (tid_now() & 127) * 16) : "memory");
    const uint32_t one = gridDim.y;
    float u0[32], u1[32], u2[32];
    float (&o0)[32] = u0, (&o1)[32] = u2, (&o2)[32] = u0;
    uint32_t fa[48];
    uint4 h[4];
    const float nz = __uint_as_float(one << 31);
    auto pack_a = [&](float (&u)[32], int c) {
        fence_regs(u);
#pragma unroll
        for (int i = 0; i < 16; i++) {
            fa[16 * c + i] = pack_bf16(c != 1 ? u[2 * i] + nz : u[2 * i], u[2 * i + 1]);
            asm volatile("" : "+r"(fa[16 * c + i])::"memory");
        }
        wg_fence();
    };
    auto pack_o = [&](float (&o)[32], [[maybe_unused]] bool first = false) {
        fence_regs(o);
        auto pk = [&](int i) { return pack_bf16(o[i], first ? o[i + 1] + nz : o[i + 1]); };
#pragma unroll
        for (int i = 0; i < 4; i++) {
            const int b = 16 * (i & 1) + 2 * (i >> 1);
            h[i] = make_uint4(pk(b), pk(b + 4), pk(b + 8), pk(b + 12));
        }
#pragma unroll
        for (int i = 0; i < 4; i++) asm volatile("" : "+r"(h[i].x), "+r"(h[i].y), "+r"(h[i].z), "+r"(h[i].w)::"memory");
    };
    TSTAMP(18);
    wg_fence();
    Gemm3s<0, 3>::run(u0, pa, dXt, one); wg_commit();
    TSTAMP(19);
    Gemm3s<1, 3>::run(u1, pa, dXt, one); wg_commit();
    Gemm3s<2, 3>::run(u2, pa, dXt, one); wg_commit();
    TSTAMP(20);
    const uint32_t t = tid_now(), slot = kSmemBase + kOffStage + (t & 96) * 64;
    const uint32_t sa = stage_addr(slot, t);
    const uint32_t tok = (t >> 3) & 3, j = t & 7, la = slot + tok * 128 + ((j ^ tok) << 4);
    char* out;
    asm volatile("ld.volatile.shared.u64 %0, [%1];" : "=l"(out) : "r"(kScAddr + 8) : "memory");
    out += (((win >> 6) * 8 + ((t >> 4) & 6)) * kHW + (win & 63) * 8 + tok) * (kC * 2) + j * 16;
    uint4 v[4];
    auto S = [&](int i, int off = 0) { stsm4((sa ^ (i & 1) * 64) + (i >> 1) * 1024 + off, h[i]); };
    auto L = [&](int i, int off = 0) {
        asm volatile("ld.volatile.shared.v4.b32 {%0, %1, %2, %3}, [%4];" : "=r"(v[i].x), "=r"(v[i].y), "=r"(v[i].z), "=r"(v[i].w)
                     : "r"((la ^ (i & 1) * 64) + i * 512 + off) : "memory");
    };
    auto G = [&](int c, int i) {
        asm volatile("st.global.v4.b32 [%0], {%1, %2, %3, %4};"
                     ::"l"(out + ((i >> 1) * kHW + 4 * (i & 1)) * (kC * 2) + c * 128), "r"(v[i].x), "r"(v[i].y), "r"(v[i].z), "r"(v[i].w) : "memory");
    };
#define W(C, K0, K1, O) Gemm4s<C, K0, K1>::run(O, fa, dWv, one)
#define PIN __syncwarp()
    wg_wait2(); TSTAMP(21); pack_a(u0, 0);
    asm volatile("bar.sync %0, 128;" ::"r"((tid_now() >> 7) + 1) : "memory");
    W(0, 0, 3, o0); wg_commit();
    wg_wait2(); TSTAMP(22); pack_a(u1, 1);
    W(0, 4, 7, o0); wg_commit();
    wg_wait2(); TSTAMP(23); pack_a(u2, 2);
    W(0, 8, 11, o0); wg_commit();
    W(1, 0, 5, o1); wg_commit();
    wg_wait1(); TSTAMP(24); pack_o(o0, true);
    W(1, 6, 6, o1); S(0); W(1, 7, 7, o1); S(1); W(1, 8, 8, o1); S(2); W(1, 9, 9, o1); S(3); W(1, 10, 10, o1); PIN; L(0); W(1, 11, 11, o1); wg_commit(); L(1);
    wg_fence();
    W(2, 0, 0, o2); L(2); W(2, 1, 1, o2); L(3); W(2, 2, 2, o2); PIN; G(0, 0); PIN; W(2, 3, 3, o2); G(0, 1); PIN; W(2, 4, 4, o2); G(0, 2); PIN; W(2, 5, 5, o2); wg_commit(); G(0, 3);
    PIN;
    wg_wait1(); TSTAMP(25); pack_o(o1);
    W(2, 6, 6, o2); S(0); W(2, 7, 7, o2); S(1); W(2, 8, 8, o2); S(2); W(2, 9, 9, o2); S(3); W(2, 10, 11, o2); wg_commit();
    wg_wait1();
    PIN; L(0); L(1); L(2); L(3); G(1, 0); G(1, 1); G(1, 2); G(1, 3);
    PIN;
    TSTAMP(26);
    wg_wait0(); TSTAMP(27); pack_o(o2);
    fence_regs(fa);
    S(0); S(1); S(2); S(3); PIN; L(0); L(1); L(2); L(3); G(2, 0); G(2, 1); G(2, 2); G(2, 3);
    TSTAMP(28);
#undef W
#undef PIN
}

__global__ void __launch_bounds__(kThreads, 1)
swin_attn_kernel(const __nv_bfloat16* __restrict__ wqkv, const __nv_bfloat16* __restrict__ wo, Scratch* __restrict__ sc, void* out,
                 const __grid_constant__ OutMaps tmo, const __grid_constant__ CUtensorMap tmx, const __grid_constant__ CUtensorMap tmp, const __grid_constant__ CUtensorMap tmc) {
    extern __shared__ uint8_t smem_raw[];
    constexpr uint32_t sbase = kSmemBase;
    if (smem_u32(smem_raw) != kSmemBase) __trap();
    const int tid = threadIdx.x, lane = tid & 31;
    const uint32_t warpu = __reduce_or_sync(0xffffffffu, (uint32_t)tid >> 5), wgu = warpu >> 2;
    const int warp = (int)warpu, wg = (int)wgu;
    const int G = gridDim.x;
    const uint32_t bar_full = sbase + kOffBar + 8 * wg;

    PROF(0); PROFG(1);
    if (wg == 0) FLOG(4096 + blockIdx.x * 4);
    const int ftile = blockIdx.x + (warp & 1) * G;
    FoldRegs fq;
#pragma unroll
    for (int j = 0; j < 6; j++) {
        asm volatile("" : "=r"(fq.B0[j].x), "=r"(fq.B0[j].y), "=r"(fq.B0[j].z), "=r"(fq.B0[j].w));
        asm volatile("" : "=r"(fq.B1[j].x), "=r"(fq.B1[j].y), "=r"(fq.B1[j].z), "=r"(fq.B1[j].w));
    }
#pragma unroll
    for (int j = 0; j < 48; j++) asm volatile("" : "=r"(fq.A[j]));
    if (warp < 2 && ftile < kTiles) fold_load_qk(fq, wqkv, ftile, lane);
    PSTAMP(0, 18);
    if (warp == 3) {
        const uint32_t i = blockIdx.x + G * (lane & 15);
        const char* p = lane < 16 ? (const char*)wo + i * 128 : (const char*)wqkv + i * 128 + (i / 3 + 1) * 768;
        if (i < 576) asm volatile("prefetch.global.L2 [%0];" ::"l"(p) : "memory");
    }
    uint32_t epoch;
    asm volatile("ld.relaxed.gpu.global.u32 %0, [%1];" : "=r"(epoch) : "l"(sc->epoch) : "memory");
    if (warp == 10) {
        if (lane == 0) {
#pragma unroll
            for (int w = 0; w < kNWG; w++) mbar_init(sbase + kOffBar + 8 * w, 1);
            asm volatile("fence.mbarrier_init.release.cluster;" ::: "memory");
        }
        __syncwarp();
        asm volatile("bar.arrive 11, 384;" ::: "memory");
        if (lane == 0) {
            const uint32_t t0 = (uint32_t)clock64() + TRK_START + ((blockIdx.x * 37) & 63) * TRK_STAG / 64;
#pragma unroll
            for (int w = 0; w < kNWG; w++) mbar_expect_tx(sbase + kOffBar + 8 * w, kXBytes);
            PSTAMP(320, 18);
#pragma unroll 1
            for (int i = 0; i < 3 * kNWG + (PF_INIT > 0); i++) {
                while ((int)((uint32_t)clock64() - t0) < (i < 3 ? i * TRK_STEP0 : TRK_MID + (i - 3) * TRK_STEP)) {}
                const int w = i / 3, c = i % 3;
                if (w < kNWG) tma_load_x_chunk(sbase + kOffX + w * kXBytes + c * 8192, &tmc, sbase + kOffBar + 8 * w, w * G + blockIdx.x, c);
                else prefetch_x(&tmp, kNWG * G + blockIdx.x);
            }
        }
    }
    if (warp < 3) {
        for (int t = ftile;;) {
            const bool on = warp < 2 && t < kTiles;
            fold_compute_store<false>(fq, sc, t, lane, epoch & 1, on);
            if (lane == 0 && on) asm volatile("red.relaxed.gpu.global.add.u32 [%0], %1;" ::"l"(sc->cnt_m), "r"(1u) : "memory");
            PSTAMP(0, 20); PSTAMP(32, 20);
            t += 2 * G;
            if (__builtin_expect(warp == 2 || t >= kTiles, 1)) break;
            fold_load_qk(fq, wqkv, t, lane);
        }
    }
    if (warp < 4) {
        asm volatile("bar.sync 11, 384;" ::: "memory");
    } else if (warp == 4) {
        if (lane == 0) {
            set_link(0, 9); set_link(1, 8); set_link(2, 8);
            asm volatile("st.shared.v2.u64 [%0], {%1, %2};" ::"r"(kScAddr), "l"(sc), "l"(out) : "memory");
            mbar_init(bar_m(0), 1);
            mbar_init(bar_m(1), 1);
            mbar_init(bar_m(2), 1);
            asm volatile("fence.mbarrier_init.release.cluster;" ::: "memory");
        }
        __syncwarp();
        asm volatile("bar.arrive 12, 128;" ::: "memory");
        asm volatile("bar.arrive 11, 384;" ::: "memory");
        if (lane == 0) {
            uint32_t v, spins = 0;
            do {
                asm volatile("ld.relaxed.gpu.global.u32 %0, [%1];" : "=r"(v) : "l"(sc->cnt_m) : "memory");
                if (++spins > (1u << 22)) __trap();
            } while (v < M_THR);
            PSTAMP(128, 21);
            const uint32_t par = epoch & 1;
            m_load(sc, 0, par); m_load(sc, 1, par); m_load(sc, 2, par);
            PSTAMP(128, 22);
        }
    } else if (warp == 11) {
        if (lane == 0) {
            mbar_init(kBarV, 1);
            asm volatile("fence.mbarrier_init.release.cluster;" ::: "memory");
        }
        __syncwarp();
        asm volatile("bar.sync 11, 384;" ::: "memory");
        if (lane == 0) {
            uint32_t v, spins = 0;
            do {
                asm volatile("ld.relaxed.gpu.global.u32 %0, [%1];" : "=r"(v) : "l"(sc->cnt_v) : "memory");
                if (++spins > (1u << 22)) __trap();
            } while (v < kTiles);
            PSTAMP(352, 23);
            { uint32_t ok = 0, n = 0;
              while (!ok && ++n < 64) asm volatile("{\n.reg .pred p;\nmbarrier.try_wait.parity.shared::cta.b64 p, [%1], 0;\nselp.b32 %0, 1, 0, p;\n}\n" : "=r"(ok) : "r"(bar_m(V_AFTER)) : "memory"); }
            v_load(sc, epoch & 1);
            PSTAMP(352, 24);
        }
    } else if (warp == 10) {
    } else if (warp >= 8) {
        asm volatile("bar.arrive 11, 384;" ::: "memory");
        if (VO_COND) { const uint32_t t0 = (uint32_t)clock64(); while ((uint32_t)clock64() - t0 < VO_DELAY) {} }
        FoldRegs fr;
        for (int t = G - 1 - blockIdx.x + (warp & 1) * G; t < kTiles; t += 2 * G) {
            const int tt = t;
            PSTAMP(256, 27);
            fold_load_vo(fr, wqkv, wo, tt, lane);
            PSTAMP(256, 28);
            fold_compute_store<true>(fr, sc, tt, lane, epoch & 1, 1);
            PSTAMP(256, 18);
            if (lane == 0) asm volatile("red.relaxed.gpu.global.add.u32 [%0], %1;" ::"l"(sc->cnt_v), "r"(1u) : "memory");
            PSTAMP(256, 19); PSTAMP(288, 19);
        }
    } else {
        asm volatile("bar.arrive 11, 384;" ::: "memory");
        asm volatile("bar.sync 12, 128;" ::: "memory");
    }
    __syncwarp();
    if (wg == 1) m_check(sc, epoch & 1);
    uint4 hv[12];
#pragma unroll
    for (int a = 0; a < 12; a++) asm volatile("" : "=r"(hv[a].x), "=r"(hv[a].y), "=r"(hv[a].z), "=r"(hv[a].w));

    constexpr uint32_t dWm = ((sbase + kOffWm) >> 4) | (1u << 16);
    constexpr uint32_t dWv = ((sbase + kOffWv) >> 4) | (1u << 16);
    const float cs = 0.07216878364870322f * 1.4426950408889634f;
    PROF(2);
    PSTAMP(0, 23);
    PROF(3);
    if (wg == 2) {
        asm volatile("bar.sync 13, 128;" ::: "memory");
        v_check(sc, epoch & 1);
        PSTAMP(256, 23);
    }
    mbar_wait(bar_full, 0);
    PSTAMP(0, 24); PSTAMP(128, 24); PSTAMP(256, 24);

    uint32_t st = (uint32_t)(wg * G + blockIdx.x) << 17 | kFirst | (wg == 0 ? kSolo : 0);

    while (true) {
        float acc[96];
        uint32_t fa[48];
        const uint32_t dX = ((sbase + kOffX + wg_uniform() * kXBytes) >> 4) | (1u << 16);
        uint32_t ticket = 0;
        STAMP(0);
        uint32_t lnk = baton_wait(st, 0);
        STAMP(1);
        while (true) {
            const bool very_first = (st & kFirst) && tid_now() < 128;
            Gemm1<11>::run(acc, dX, dWm, very_first, st);
            wg_commit();
            if (!very_first) { baton_pass(lnk, st); break; }
            wg_wait0();
            if (m_agree(1)) break;
            st ^= kRound;
        }
        STAMP(2);
        if (!(st & kFirst)) {
            const uint32_t w4 = warp4_uniform();
            const uint32_t slot = sbase + kOffStage + w4 * 2048;
            const int col = (st_out(st) & 63) * 8, row = (st_out(st) >> 6) * 8 + 2 * w4;
            store_round<0>(hv, slot, tmo.m, col, row);
            bulk_wait_read(); __syncwarp();
            store_round<1>(hv, slot, tmo.m, col, row);
            bulk_wait_read(); __syncwarp();
            store_round<2>(hv, slot, tmo.m, col, row);
        }
        if ((st & kFirst) && (tid_now() == 128 || (PF_INIT > 2 && tid_now() == 256))) prefetch_x(&tmp, (kNWG + (tid_now() >> 7)) * gridDim.x + blockIdx.x);
        __syncwarp();
        draw_ticket(ticket);
        wg_wait0();
        STAMP(3);
        fence_regs(acc);
#pragma unroll
        for (int i = 0; i < 48; i++) fa[i] = pack_bf16(acc[2 * i], acc[2 * i + 1]);

        float s[32];
        fence_regs(fa);
        bulk_wait_read();
        STAMP(4);
        lnk = baton_wait(st, fa[47]);
        STAMP(5);
        wg_fence();
        Gemm2<11>::run(s, fa, dX, lnk, st);
        wg_commit();
        STAMP(6);
        wg_wait0();
        FLOG(st_win(st));
        STAMP(7);
        fence_regs(s);
        fence_regs(fa);

        uint32_t pa[16];
        {
            float a0[8], a1[8];
#pragma unroll
            for (int j = 0; j < 8; j++) { a0[j] = fmaxf(s[4 * j], s[4 * j + 1]); a1[j] = fmaxf(s[4 * j + 2], s[4 * j + 3]); }
#pragma unroll
            for (int d = 4; d > 0; d >>= 1)
#pragma unroll
                for (int j = 0; j < d; j++) { a0[j] = fmaxf(a0[j], a0[j + d]); a1[j] = fmaxf(a1[j], a1[j + d]); }
            float m0 = a0[0], m1 = a1[0];
            m0 = fmaxf(m0, __shfl_xor_sync(0xffffffffu, m0, 1));
            m1 = fmaxf(m1, __shfl_xor_sync(0xffffffffu, m1, 1));
            m0 = fmaxf(m0, __shfl_xor_sync(0xffffffffu, m0, 2));
            m1 = fmaxf(m1, __shfl_xor_sync(0xffffffffu, m1, 2));
            m0 *= cs; m1 *= cs;
            float l0 = 0.f, l1 = 0.f;
#pragma unroll
            for (int j = 0; j < 8; j++) {
                s[4 * j]     = ex2(fmaf(s[4 * j], cs, -m0));
                s[4 * j + 1] = ex2(fmaf(s[4 * j + 1], cs, -m0));
                s[4 * j + 2] = ex2(fmaf(s[4 * j + 2], cs, -m1));
                s[4 * j + 3] = ex2(fmaf(s[4 * j + 3], cs, -m1));
                l0 += s[4 * j] + s[4 * j + 1];
                l1 += s[4 * j + 2] + s[4 * j + 3];
            }
            l0 += __shfl_xor_sync(0xffffffffu, l0, 1);
            l1 += __shfl_xor_sync(0xffffffffu, l1, 1);
            l0 += __shfl_xor_sync(0xffffffffu, l0, 2);
            l1 += __shfl_xor_sync(0xffffffffu, l1, 2);
            const float r0 = rcp(l0), r1 = rcp(l1);
#pragma unroll
            for (int j = 0; j < 8; j++) {
                pa[2 * j]     = pack_bf16(s[4 * j] * r0, s[4 * j + 1] * r0);
                pa[2 * j + 1] = pack_bf16(s[4 * j + 2] * r1, s[4 * j + 3] * r1);
            }
        }

        fence_regs(pa);
        if ((tid_now() & 127) == 0)
            asm volatile("st.volatile.shared.u32 [%0], %1;" ::"r"(kLink + 4 + 8 * (tid_now() >> 7)), "r"(kNWG * gridDim.x + ticket) : "memory");
        STAMP(8);
        uint32_t pub;
        lnk = baton_wait_pub(st, pa[15], pub);
        if ((st & kFirst) && tid_now() == 0) set_link(1, 10);
        STAMP(9);
        const bool alone = ALONE_COND;
        asm volatile("{\n.reg .pred p;\nsetp.ne.u32 p, %16, 0;\n"
                     "@p st.volatile.shared.v4.b32 [%17], {%0, %1, %2, %3};\n@p st.volatile.shared.v4.b32 [%17 + 2048], {%4, %5, %6, %7};\n"
                     "@p st.volatile.shared.v4.b32 [%17 + 4096], {%8, %9, %10, %11};\n@p st.volatile.shared.v4.b32 [%17 + 6144], {%12, %13, %14, %15};\n}\n"
                     :: "r"(pa[0]), "r"(pa[1]), "r"(pa[2]), "r"(pa[3]), "r"(pa[4]), "r"(pa[5]), "r"(pa[6]), "r"(pa[7]),
                        "r"(pa[8]), "r"(pa[9]), "r"(pa[10]), "r"(pa[11]), "r"(pa[12]), "r"(pa[13]), "r"(pa[14]), "r"(pa[15]),
                        "r"((uint32_t)alone), "r"(sbase + kOffStage + (tid_now() & 127) * 16) : "memory");
        if (alone) {
            if (ticket == kNWin - 1) reset_for_next_launch();
            __syncwarp();
            finish_alone(dX + (((8192u >> 4) - 1) << 16), dWv, tmo.m, st_win(st));
            FLOG(4096 + blockIdx.x * 4 + 1 + (tid_now() >> 7));
            PROF(4); PROFG(5);
            return;
        }
        wg_fence();
        Gemm3<3>::run(acc, pa, dX + (((8192u >> 4) - 1) << 16));
        wg_commit();
        baton_pass(lnk, st);
        STAMP(10);
        const int nxt = (int)__reduce_or_sync(0xffffffffu, pub);
        wg_wait0();
        STAMP(11);
        fence_regs(acc);
        fence_regs(pa);

        if (((tid_now() >> 5) & 3) == 0 && nxt < kNWin) {
            asm volatile("bar.sync %0, 128;" ::"r"((tid_now() >> 7) + 1) : "memory");
            if (elect_one()) {
                const uint32_t wgl = tid_now() >> 7;
                const uint32_t bar = sbase + kOffBar + 8 * wgl;
                mbar_expect_tx(bar, kXBytes);
                tma_load_x(sbase + kOffX + wgl * kXBytes, &tmx, bar, nxt);
            }
            __syncwarp();
        } else {
            asm volatile("bar.arrive %0, 128;" ::"r"((tid_now() >> 7) + 1) : "memory");
        }
#pragma unroll
        for (int i = 0; i < 48; i++) fa[i] = pack_bf16(acc[2 * i], acc[2 * i + 1]);

        asm volatile("st.volatile.shared.v4.b32 [%4], {%0, %1, %2, %3};"
                     :: "r"(fa[44]), "r"(fa[45]), "r"(fa[46]), "r"(fa[47]), "r"(sbase + kOffStash + (tid_now() & 127) * 16) : "memory");
        fence_regs(fa);
        STAMP(12);
        lnk = baton_wait(st, fa[43]);
        STAMP(13);
        if (nxt >= kNWin) {
            if ((tid_now() & 127) == 0) {
#pragma unroll
                for (int w = 0; w < kNWG; w++) {
                    uint32_t l;
                    asm volatile("ld.volatile.shared.u32 %0, [%1];" : "=r"(l) : "r"(kLink + 8 * w) : "memory");
                    if (l == (tid_now() >> 7) + 8) set_link(w, lnk);
                }
            }
        }
        __syncwarp();
        wg_fence();
        Gemm4<0, 1>::run(acc, fa, dWv);
        wg_commit();
        Gemm4<2, 10>::run(acc, fa, dWv);
        wg_commit();
        wg_wait1();
        uint32_t fl[4];
        asm volatile("ld.volatile.shared.v4.b32 {%0, %1, %2, %3}, [%4];"
                     : "=r"(fl[0]), "=r"(fl[1]), "=r"(fl[2]), "=r"(fl[3]) : "r"(sbase + kOffStash + (tid_now() & 127) * 16) : "memory");
        wg_fence();
        wg192_rs<false, 0, koff(11, 24576)>(acc, fl, dWv);
        wg_commit();
        baton_pass(lnk, st);
        STAMP(14);
        if (((tid_now() >> 5) & 3) == 0) {
            if (elect_one()) {
                const int base = kNWG * (int)gridDim.x, t = nxt - base;
                auto lead = [&](int tt) { return min(min(PF_INIT * (int)gridDim.x + ((tt * PF_UP) >> 8), PF_LEAD), max(((kNWin - base - tt) * PF_DOWN) >> 8, PF_MIN)); };
                const int hi = base + t + lead(t);
                int lo = max(max(base + t - 1 + lead(t - 1), base + t) + 1, base + PF_INIT * (int)gridDim.x);
#pragma unroll 1
                for (; lo <= hi && lo < kNWin; lo++) prefetch_x(&tmp, lo);
                if (t == kNWin - 1) reset_for_next_launch();
            }
            __syncwarp();
        }
        const int win_next = nxt;
        st = ((st ^ kPhase) & (kPhase | kSolo)) | st_win(st) << 4 | win_next << 17;
        if (win_next < kNWin) mbar_wait(sbase + kOffBar + 8 * (tid_now() >> 7), st & kPhase);
        wg_wait0();
        STAMP(15);
        fence_regs(acc);
        fence_regs(fa);
        fence_regs(fl);

        {
#pragma unroll
            for (int a = 0; a < 6; a++) {
                hv[2 * a].x     = pack_bf16(acc[16 * a + 0], acc[16 * a + 1]);
                hv[2 * a].y     = pack_bf16(acc[16 * a + 4], acc[16 * a + 5]);
                hv[2 * a].z     = pack_bf16(acc[16 * a + 8], acc[16 * a + 9]);
                hv[2 * a].w     = pack_bf16(acc[16 * a + 12], acc[16 * a + 13]);
                hv[2 * a + 1].x = pack_bf16(acc[16 * a + 2], acc[16 * a + 3]);
                hv[2 * a + 1].y = pack_bf16(acc[16 * a + 6], acc[16 * a + 7]);
                hv[2 * a + 1].z = pack_bf16(acc[16 * a + 10], acc[16 * a + 11]);
                hv[2 * a + 1].w = pack_bf16(acc[16 * a + 14], acc[16 * a + 15]);
            }
        }
        STAMP(16);
        if (win_next >= kNWin) break;
    }
    asm volatile("bar.sync %0, 128;" ::"r"((tid_now() >> 7) + 1) : "memory");
    {
        const uint32_t t = tid_opaque(), wu = __reduce_or_sync(0xffffffffu, t >> 5), w4 = wu & 3;
        const uint32_t slot = sbase + kOffX + wu * 6144, sa = stage_addr(slot, t);
        const int col = (st_out(st) & 63) * 8, row = (st_out(st) >> 6) * 8 + 2 * w4;
        stage_round<0>(hv, sa);
        stage_round<1>(hv, sa + 2048);
        stage_round<2>(hv, sa + 4096);
        stage_fence();
        send_round<0>(slot, tmo.m, col, row);
        send_round<1>(slot + 2048, tmo.m, col, row);
        send_round<2>(slot + 4096, tmo.m, col, row);
    }
    bulk_wait_read();
    FLOG(4096 + blockIdx.x * 4 + 1 + (tid_now() >> 7));
    PROF(4); PROFG(5);
    PROF_FLUSH();
}

typedef CUresult (*EncodeTiledFn)(CUtensorMap*, CUtensorMapDataType, cuuint32_t, void*, const cuuint64_t*,
                                  const cuuint64_t*, const cuuint32_t*, const cuuint32_t*, CUtensorMapInterleave,
                                  CUtensorMapSwizzle, CUtensorMapL2promotion, CUtensorMapFloatOOBfill);

}

extern "C" void kernel_launch(void* const* d_in, const int* in_sizes, int n_in, void* d_out, int out_size) {
    (void)in_sizes; (void)n_in; (void)out_size;
    const __nv_bfloat16* x    = (const __nv_bfloat16*)d_in[0];
    const __nv_bfloat16* wqkv = (const __nv_bfloat16*)d_in[1];
    const __nv_bfloat16* wo   = (const __nv_bfloat16*)d_in[2];

    static EncodeTiledFn encode = nullptr;
    static int num_sms = 0;
    static Scratch* scratch = nullptr;
    if (!encode) {
        void* fn = nullptr;
        cudaDriverEntryPointQueryResult qr;
        cudaGetDriverEntryPoint("cuTensorMapEncodeTiled", &fn, cudaEnableDefault, &qr);
        encode = (EncodeTiledFn)fn;
        cudaGetSymbolAddress((void**)&scratch, g_scratch);
        int dev = 0;
        cudaGetDevice(&dev);
        cudaDeviceGetAttribute(&num_sms, cudaDevAttrMultiProcessorCount, dev);
        cudaFuncSetAttribute(swin_attn_kernel, cudaFuncAttributeMaxDynamicSharedMemorySize, kSmemBytes);
    }
    CUtensorMap tmx;
    const cuuint64_t gdim[4] = {64, (cuuint64_t)kHW, (cuuint64_t)kHW, 3};
    const cuuint64_t gstr[3] = {(cuuint64_t)kC * 2, (cuuint64_t)kHW * kC * 2, 128};
    const cuuint32_t box[4] = {64, 8, 8, 3};
    const cuuint32_t estr[4] = {1, 1, 1, 1};
    encode(&tmx, CU_TENSOR_MAP_DATA_TYPE_BFLOAT16, 4, (void*)x, gdim, gstr, box, estr, CU_TENSOR_MAP_INTERLEAVE_NONE,
           CU_TENSOR_MAP_SWIZZLE_128B, CU_TENSOR_MAP_L2_PROMOTION_NONE, CU_TENSOR_MAP_FLOAT_OOB_FILL_NONE);

    CUtensorMap tmp;
    const cuuint64_t pdim[3] = {(cuuint64_t)kC, (cuuint64_t)kHW, (cuuint64_t)kHW};
    const cuuint64_t pstr[2] = {(cuuint64_t)kC * 2, (cuuint64_t)kHW * kC * 2};
    const cuuint32_t pbox[3] = {(cuuint32_t)kC, 8, 8};
    encode(&tmp, CU_TENSOR_MAP_DATA_TYPE_BFLOAT16, 3, (void*)x, pdim, pstr, pbox, estr, CU_TENSOR_MAP_INTERLEAVE_NONE,
           CU_TENSOR_MAP_SWIZZLE_NONE, CU_TENSOR_MAP_L2_PROMOTION_NONE, CU_TENSOR_MAP_FLOAT_OOB_FILL_NONE);
    CUtensorMap tmc;
    const cuuint32_t boxc[4] = {64, 8, 8, 1};
    encode(&tmc, CU_TENSOR_MAP_DATA_TYPE_BFLOAT16, 4, (void*)x, gdim, gstr, boxc, estr, CU_TENSOR_MAP_INTERLEAVE_NONE,
           CU_TENSOR_MAP_SWIZZLE_128B, CU_TENSOR_MAP_L2_PROMOTION_NONE, CU_TENSOR_MAP_FLOAT_OOB_FILL_NONE);
    OutMaps tmo;
    const cuuint32_t boxo[4] = {64, 8, 1, 2};
    encode(&tmo.m[0], CU_TENSOR_MAP_DATA_TYPE_BFLOAT16, 4, d_out, gdim, gstr, boxo, estr, CU_TENSOR_MAP_INTERLEAVE_NONE,
           CU_TENSOR_MAP_SWIZZLE_128B, CU_TENSOR_MAP_L2_PROMOTION_NONE, CU_TENSOR_MAP_FLOAT_OOB_FILL_NONE);
    const cuuint64_t odim[4] = {64, (cuuint64_t)kHW, (cuuint64_t)kHW, 2};
    const cuuint64_t ostr[3] = {(cuuint64_t)kC * 2, (cuuint64_t)kHW * kC * 2, (cuuint64_t)kHW * kC * 2 - 256};
    encode(&tmo.m[1], CU_TENSOR_MAP_DATA_TYPE_BFLOAT16, 4, (char*)d_out + 256, odim, ostr, boxo, estr, CU_TENSOR_MAP_INTERLEAVE_NONE,
           CU_TENSOR_MAP_SWIZZLE_128B, CU_TENSOR_MAP_L2_PROMOTION_NONE, CU_TENSOR_MAP_FLOAT_OOB_FILL_NONE);
    swin_attn_kernel<<<num_sms, kThreads, kSmemBytes, cudaStreamPerThread>>>(wqkv, wo, scratch, d_out, tmo, tmx, tmp, tmc);
}
```

```cpp
#include <cuda_runtime.h>
#include <cuda_bf16.h>
#include <cuda.h>
#include <stdint.h>
#include <stddef.h>

#define TICKET_AT 0
#define G4_PASS 11
#define RT_ARG
#define RT_EF , LD_EF_FROM
namespace {

constexpr int kC      = 192;
constexpr int kHW     = 512;
#define MAXWIN 4096
constexpr int kNWin   = MAXWIN;
constexpr int kXBytes = 64 * kC * 2;
constexpr int kWBytes = kC * kC * 2;
constexpr int kNWG    = 3;
constexpr int kThreads = kNWG * 128;
constexpr int kTiles  = 144;
#define TRK_STEP 500
#define TRK_START 100
#define TRK_STAG 500
#define TRK_STEP0 750
#define TRK_MID 2400
#define PF_INIT 2
#define PF_UP 160
#define PF_PEAK 400
#define PF_T1 800
#define PF_D1 40
#define PF_LEAD 300
#define PF_DOWN 12
#define PF_MIN 140

constexpr int kOffWm  = 0;
constexpr int kOffWv  = kWBytes;
constexpr int kOffX   = 2 * kWBytes;
constexpr int kOffStage = kOffX + kNWG * kXBytes;
constexpr int kOffStash = kOffStage + 8192;
constexpr int kOffBar = kOffStash + 2048;
constexpr int kOffProf = kOffBar + 128;
constexpr int kSmemBytes = kOffProf;
constexpr uint32_t kSmemBase = 1024;

struct Scratch {
    uint32_t ticket[32];
    uint32_t epoch[32];
    uint32_t cnt_v[32];
    uint32_t cnt_m[32];
    uint4 img[2][2][kWBytes / 16];
};
__device__ __align__(128) Scratch g_scratch;

#define PROF(slot)
#define PROFG(slot)
#define PROFT(t, slot)
#define PROF_FLUSH()
#define STAMP(slot)
#define TSTAMP(slot)
#define PSTAMP(t, slot)
#define V_AFTER 2
#define VO_DELAY 700
#ifndef M_THR
#define M_THR 72
#endif
#define POLL_AT 0
#define VO_MODE 0
#define VO_COND (warp == 9)
#define FLOG(idx)
__device__ __forceinline__ uint32_t smem_u32(const void* p) { return (uint32_t)__cvta_generic_to_shared(p); }

__device__ __forceinline__ void mbar_init(uint32_t bar, uint32_t count) {
    asm volatile("mbarrier.init.shared::cta.b64 [%0], %1;" ::"r"(bar), "r"(count) : "memory");
}
__device__ __forceinline__ void mbar_expect_tx(uint32_t bar, uint32_t bytes) {
    asm volatile("mbarrier.arrive.expect_tx.shared::cta.b64 _, [%0], %1;" ::"r"(bar), "r"(bytes) : "memory");
}
__device__ __forceinline__ void mbar_wait(uint32_t bar, uint32_t parity) {
    uint32_t ok;
    uint32_t spins = 0;
    do {
        asm volatile("{\n.reg .pred p;\n"
                     "mbarrier.try_wait.parity.shared::cta.b64 p, [%1], %2;\n"
                     "selp.b32 %0, 1, 0, p;\n}\n"
                     : "=r"(ok) : "r"(bar), "r"(parity) : "memory");
        if (++spins > (1u << 26)) __trap();
    } while (!ok);
}
__device__ __forceinline__ uint32_t tid_now() {
    uint32_t t;
    asm volatile("mov.u32 %0, %%tid.x;" : "=r"(t));
    return t;
}
__device__ __forceinline__ bool elect_one() {
    uint32_t pred;
    asm volatile("{\n.reg .pred p;\nelect.sync _|p, 0xffffffff;\nselp.b32 %0, 1, 0, p;\n}\n" : "=r"(pred));
    return pred != 0;
}
__device__ __forceinline__ uint32_t wg_uniform() { return __reduce_or_sync(0xffffffffu, tid_now() >> 7); }
constexpr uint32_t kLink = kSmemBase + kOffBar + 64;
constexpr uint32_t kPhase = 1;
constexpr uint32_t kSolo = 2;
constexpr uint32_t kFirst = 4;
constexpr uint32_t kVeryFirst = 1u << 16;
constexpr uint32_t kRound = 8;
__device__ __forceinline__ int st_out(uint32_t st) { return (st >> 4) & 0xfff; }
__device__ __forceinline__ int st_win(uint32_t st) { return st >> 17; }
__device__ __forceinline__ uint32_t baton_wait(uint32_t st, uint32_t packed) {
    if (packed == 0xffffffffu) __trap();
    if (!(st & kSolo)) asm volatile("bar.sync %0, 256;" ::"r"((tid_now() >> 7) + 8) : "memory");
    uint32_t lnk;
    asm volatile("ld.volatile.shared.u32 %0, [%1];" : "=r"(lnk) : "r"(kLink + 8 * (tid_now() >> 7)) : "memory");
    return lnk;
}
__device__ __forceinline__ uint32_t baton_wait_pub(uint32_t st, uint32_t packed, uint32_t& pub) {
    if (packed == 0xffffffffu) __trap();
    asm volatile("bar.sync %0, %1;" ::"r"((tid_now() >> 7) + 8), "r"(st & kSolo ? 128 : 256) : "memory");
    uint32_t lnk;
    asm volatile("ld.volatile.shared.v2.u32 {%0, %1}, [%2];" : "=r"(lnk), "=r"(pub) : "r"(kLink + 8 * (tid_now() >> 7)) : "memory");
    return lnk;
}
__device__ __forceinline__ void baton_pass(uint32_t lnk, uint32_t& st) {
    const bool other = lnk != (tid_now() >> 7) + 8;
    if (other) asm volatile("bar.arrive %0, 256;" ::"r"(lnk) : "memory");
    st = other ? st & ~kSolo : st | kSolo;
}
__device__ __forceinline__ void set_link(int w, uint32_t v) { asm volatile("st.volatile.shared.u32 [%0], %1;" ::"r"(kLink + 8 * w), "r"(v) : "memory"); }
#define LD_EF_FROM 3100
constexpr uint64_t kPolNormal = 0x1000000000000000ull, kPolFirst = 0x12F0000000000000ull;
__device__ __forceinline__ void tma_load_x(uint32_t dst, const CUtensorMap* tm, uint32_t bar, int win, int ef_from) {
    const int wh = win >> 6, ww = win & 63;
    asm volatile("cp.async.bulk.tensor.4d.shared::cluster.global.mbarrier::complete_tx::bytes.L2::cache_hint"
                 " [%0], [%1, {%3, %4, %5, %6}], [%2], %7;"
                 ::"r"(dst), "l"(tm), "r"(bar), "r"(0), "r"(ww * 8), "r"(wh * 8), "r"(0), "l"(win >= ef_from ? kPolFirst : kPolNormal) : "memory");
}
__device__ __forceinline__ void tma_load_x_chunk(uint32_t dst, const CUtensorMap* tm, uint32_t bar, int win, int chunk) {
    const int wh = win >> 6, ww = win & 63;
    asm volatile("cp.async.bulk.tensor.4d.shared::cluster.global.mbarrier::complete_tx::bytes"
                 " [%0], [%1, {%3, %4, %5, %6}], [%2];"
                 ::"r"(dst), "l"(tm), "r"(bar), "r"(0), "r"(ww * 8), "r"(wh * 8), "r"(chunk) : "memory");
}
__device__ __forceinline__ void bulk_load(uint32_t dst, const void* src, uint32_t bytes, uint32_t bar) {
    asm volatile("cp.async.bulk.shared::cluster.global.mbarrier::complete_tx::bytes [%0], [%1], %2, [%3];"
                 ::"r"(dst), "l"(src), "r"(bytes), "r"(bar) : "memory");
}

__device__ __forceinline__ void wg_fence()  { asm volatile("wgmma.fence.sync.aligned;" ::: "memory"); }
__device__ __forceinline__ void wg_commit() { asm volatile("wgmma.commit_group.sync.aligned;" ::: "memory"); }
__device__ __forceinline__ void wg_wait0()  { asm volatile("wgmma.wait_group.sync.aligned 0;" ::: "memory"); }
__device__ __forceinline__ void wg_wait1()  { asm volatile("wgmma.wait_group.sync.aligned 1;" ::: "memory"); }
__device__ __forceinline__ void wg_wait2()  { asm volatile("wgmma.wait_group.sync.aligned 2;" ::: "memory"); }

template <int N> __device__ __forceinline__ void fence_regs(float (&d)[N]) {
#pragma unroll
    for (int i = 0; i < N; i++) asm volatile("" : "+f"(d[i])::"memory");
}
template <int N> __device__ __forceinline__ void fence_regs(uint32_t (&d)[N]) {
#pragma unroll
    for (int i = 0; i < N; i++) asm volatile("" : "+r"(d[i])::"memory");
}

#define ACC8(c, d, i) c(d[i]), c(d[i + 1]), c(d[i + 2]), c(d[i + 3]), c(d[i + 4]), c(d[i + 5]), c(d[i + 6]), c(d[i + 7])
#define ACC32(c, d) ACC8(c, d, 0), ACC8(c, d, 8), ACC8(c, d, 16), ACC8(c, d, 24)
#define ACC96(c, d) ACC32(c, d), ACC8(c, d, 32), ACC8(c, d, 40), ACC8(c, d, 48), ACC8(c, d, 56), \
                    ACC8(c, d, 64), ACC8(c, d, 72), ACC8(c, d, 80), ACC8(c, d, 88)
#define C_IO(x) "+f"(x)
#define C_O(x) "=f"(x)
#define REGS32 "{%0, %1, %2, %3, %4, %5, %6, %7, %8, %9, %10, %11, %12, %13, %14, %15, " \
               "%16, %17, %18, %19, %20, %21, %22, %23, %24, %25, %26, %27, %28, %29, %30, %31}"
#define REGS96 "{%0, %1, %2, %3, %4, %5, %6, %7, %8, %9, %10, %11, %12, %13, %14, %15, " \
               "%16, %17, %18, %19, %20, %21, %22, %23, %24, %25, %26, %27, %28, %29, %30, %31, " \
               "%32, %33, %34, %35, %36, %37, %38, %39, %40, %41, %42, %43, %44, %45, %46, %47, " \
               "%48, %49, %50, %51, %52, %53, %54, %55, %56, %57, %58, %59, %60, %61, %62, %63, " \
               "%64, %65, %66, %67, %68, %69, %70, %71, %72, %73, %74, %75, %76, %77, %78, %79, " \
               "%80, %81, %82, %83, %84, %85, %86, %87, %88, %89, %90, %91, %92, %93, %94, %95}"

#define DESC_HI "0x40000040"
#define MK_DESC(name, lo, off) "add.u32 t, " lo ", " off ";\nmov.b64 " name ", {t, " DESC_HI "};\n"

template <bool First, int OA, int OB> __device__ __forceinline__ void wg192_ss(float (&d)[96], uint32_t la, uint32_t lb) {
    if constexpr (First)
        asm volatile("{\n.reg .pred p;\n.reg .b32 t;\n.reg .b64 da, db;\nsetp.ne.b32 p, 0, 0;\n"
                     MK_DESC("da", "%96", "%98") MK_DESC("db", "%97", "%99")
                     "wgmma.mma_async.sync.aligned.m64n192k16.f32.bf16.bf16 " REGS96 ", da, db, p, 1, 1, 0, 0;\n}\n"
                     : ACC96(C_O, d) : "r"(la), "r"(lb), "n"(OA), "n"(OB));
    else
        asm volatile("{\n.reg .pred p;\n.reg .b32 t;\n.reg .b64 da, db;\nsetp.ne.b32 p, 1, 0;\n"
                     MK_DESC("da", "%96", "%98") MK_DESC("db", "%97", "%99")
                     "wgmma.mma_async.sync.aligned.m64n192k16.f32.bf16.bf16 " REGS96 ", da, db, p, 1, 1, 0, 0;\n}\n"
                     : ACC96(C_IO, d) : "r"(la), "r"(lb), "n"(OA), "n"(OB));
}
template <bool First, int TB, int OB> __device__ __forceinline__ void wg192_rs(float (&d)[96], const uint32_t* a, uint32_t lb) {
    if constexpr (First)
        asm volatile("{\n.reg .pred p;\n.reg .b32 t;\n.reg .b64 db;\nsetp.ne.b32 p, 0, 0;\n"
                     MK_DESC("db", "%100", "%102")
                     "wgmma.mma_async.sync.aligned.m64n192k16.f32.bf16.bf16 " REGS96 ", {%96, %97, %98, %99}, db, p, 1, 1, %101;\n}\n"
                     : ACC96(C_O, d) : "r"(a[0]), "r"(a[1]), "r"(a[2]), "r"(a[3]), "r"(lb), "n"(TB), "n"(OB));
    else
        asm volatile("{\n.reg .pred p;\n.reg .b32 t;\n.reg .b64 db;\nsetp.ne.b32 p, 1, 0;\n"
                     MK_DESC("db", "%100", "%102")
                     "wgmma.mma_async.sync.aligned.m64n192k16.f32.bf16.bf16 " REGS96 ", {%96, %97, %98, %99}, db, p, 1, 1, %101;\n}\n"
                     : ACC96(C_IO, d) : "r"(a[0]), "r"(a[1]), "r"(a[2]), "r"(a[3]), "r"(lb), "n"(TB), "n"(OB));
}
template <bool First, int TB, int OB> __device__ __forceinline__ void wg64_rs(float (&d)[32], const uint32_t* a, uint32_t lb) {
    if constexpr (First)
        asm volatile("{\n.reg .pred p;\n.reg .b32 t;\n.reg .b64 db;\nsetp.ne.b32 p, 0, 0;\n"
                     MK_DESC("db", "%36", "%38")
                     "wgmma.mma_async.sync.aligned.m64n64k16.f32.bf16.bf16 " REGS32 ", {%32, %33, %34, %35}, db, p, 1, 1, %37;\n}\n"
                     : ACC32(C_O, d) : "r"(a[0]), "r"(a[1]), "r"(a[2]), "r"(a[3]), "r"(lb), "n"(TB), "n"(OB));
    else
        asm volatile("{\n.reg .pred p;\n.reg .b32 t;\n.reg .b64 db;\nsetp.ne.b32 p, 1, 0;\n"
                     MK_DESC("db", "%36", "%38")
                     "wgmma.mma_async.sync.aligned.m64n64k16.f32.bf16.bf16 " REGS32 ", {%32, %33, %34, %35}, db, p, 1, 1, %37;\n}\n"
                     : ACC32(C_IO, d) : "r"(a[0]), "r"(a[1]), "r"(a[2]), "r"(a[3]), "r"(lb), "n"(TB), "n"(OB));
}
#define HI_OP "n"(0x40000040)
template <int Acc, int TB, int OB> __device__ __forceinline__ void wg64_last(float (&d)[32], const uint32_t* a, uint32_t lb, uint32_t hi, uint32_t one) {
    if constexpr (Acc == 0)
        asm volatile("{\n.reg .pred p;\n.reg .b32 t;\n.reg .b64 db;\nsetp.ne.b32 p, 0, 0;\nadd.u32 t, %36, %38;\nmov.b64 db, {t, %39};\n"
                     "wgmma.mma_async.sync.aligned.m64n64k16.f32.bf16.bf16 " REGS32 ", {%32, %33, %34, %35}, db, p, 1, 1, %37;\n}\n"
                     : ACC32(C_O, d) : "r"(a[0]), "r"(a[1]), "r"(a[2]), "r"(a[3]), "r"(lb), "n"(TB), "n"(OB), HI_OP);
    else if constexpr (Acc == 1)
        asm volatile("{\n.reg .pred p;\n.reg .b32 t;\n.reg .b64 db;\nsetp.ne.b32 p, 1, 0;\nadd.u32 t, %36, %38;\nmov.b64 db, {t, %39};\n"
                     "wgmma.mma_async.sync.aligned.m64n64k16.f32.bf16.bf16 " REGS32 ", {%32, %33, %34, %35}, db, p, 1, 1, %37;\n}\n"
                     : ACC32(C_IO, d) : "r"(a[0]), "r"(a[1]), "r"(a[2]), "r"(a[3]), "r"(lb), "n"(TB), "n"(OB), HI_OP);
    else
        asm volatile("{\n.reg .pred p;\n.reg .b32 t;\n.reg .b64 db;\nsetp.ne.b32 p, %40, 1;\nadd.u32 t, %36, %38;\nmov.b64 db, {t, %39};\n"
                     "wgmma.mma_async.sync.aligned.m64n64k16.f32.bf16.bf16 " REGS32 ", {%32, %33, %34, %35}, db, p, 1, 1, %37;\n}\n"
                     : ACC32(C_IO, d) : "r"(a[0]), "r"(a[1]), "r"(a[2]), "r"(a[3]), "r"(lb), "n"(TB), "n"(OB), HI_OP, "r"(one));
}
__host__ __device__ constexpr int koff(int kk, int chunk) { return ((kk >> 2) * chunk + (kk & 3) * 32) >> 4; }

__device__ __forceinline__ void stsm4(uint32_t addr, const uint4& v) {
    asm volatile("stmatrix.sync.aligned.m8n8.x4.shared.b16 [%0], {%1, %2, %3, %4};" ::"r"(addr), "r"(v.x), "r"(v.y), "r"(v.z), "r"(v.w) : "memory");
}
__device__ __forceinline__ void bulk_wait_read() {
    asm volatile("cp.async.bulk.wait_group.read 0;" ::: "memory");
}
__device__ __forceinline__ uint32_t stage_addr(uint32_t slot, uint32_t l) { return slot + (l & 7) * 128 + ((((l >> 3) & 3) ^ (l & 7)) << 4); }
__device__ __forceinline__ uint32_t tid_opaque() { return __shfl_sync(0xffffffffu, tid_now(), tid_now() & 31); }
template <int R> __device__ __forceinline__ void stage_round(const uint4 (&h)[12], uint32_t sa) {
#pragma unroll
    for (int i = 0; i < 2; i++) {
        const int r = (2 * R + i) / 3, c = (2 * R + i) % 3;
        stsm4(sa + i * 1024, h[4 * c + r]);
        stsm4((sa ^ 64) + i * 1024, h[4 * c + 2 + r]);
    }
}
__device__ __forceinline__ void stage_fence() {
    asm volatile("fence.proxy.async.shared::cta;" ::: "memory");
    __syncwarp();
}
template <int R> __device__ __forceinline__ void send_round(uint32_t slot, const CUtensorMap* tm, int col, int row) {
    asm volatile("{\n.reg .pred p;\nelect.sync _|p, 0xffffffff;\n"
                 "@p cp.async.bulk.tensor.4d.global.shared::cta.bulk_group [%0, {%2, %3, %4, %5}], [%1];\n"
                 "@p cp.async.bulk.commit_group;\n}\n"
                 ::"l"(tm + (R == 1)), "r"(slot), "r"(0), "r"(col), "r"(row + (R == 2)), "r"((int)(R == 2)) : "memory");
}
template <int R> __device__ __forceinline__ void store_round(const uint4 (&h)[12], uint32_t slot, const CUtensorMap* tm, int col, int row) {
    stage_round<R>(h, stage_addr(slot, tid_now()));
    stage_fence();
    send_round<R>(slot, tm, col, row);
}
__device__ __forceinline__ uint32_t warp4_uniform() { return __reduce_or_sync(0xffffffffu, (tid_now() >> 5) & 3); }
struct OutMaps { CUtensorMap m[2]; };
__host__ __device__ constexpr uint32_t bar_m(int c) { return kSmemBase + kOffBar + 32 + 8 * c; }
__device__ __forceinline__ void m_load(const Scratch* sc, int c, uint32_t par) {
    mbar_expect_tx(bar_m(c), 24576);
    bulk_load(kSmemBase + kOffWm + c * 24576, sc->img[par][0] + c * 1536, 24576, bar_m(c));
}
__device__ __forceinline__ bool m_agree(uint32_t ok) {
    uint32_t all;
    asm volatile("{\n.reg .pred p, q;\nsetp.ne.u32 p, %1, 0;\nbar.red.and.pred q, 7, 256, p;\nselp.b32 %0, 1, 0, q;\n}\n" : "=r"(all) : "r"(ok) : "memory");
    return all != 0;
}
__device__ __forceinline__ void m_check(const Scratch* sc, uint32_t par) {
    for (uint32_t round = 0;; round++) {
        uint32_t m = ~0u;
#pragma unroll 1
        for (int c = 0; c < 3; c++) {
            mbar_wait(bar_m(c), round & 1);
#pragma unroll
            for (int j = 0; j < 6; j++) {
                uint32_t v;
                asm volatile("ld.volatile.shared.b32 %0, [%1];" : "=r"(v)
                             : "r"(kSmemBase + kOffWm + c * 24576 + 4096 * j + (tid_now() & 127) * 32 + (tid_now() & 28)) : "memory");
                m = min(m, v);
            }
        }
        if (m_agree(m)) break;
        if (round > (1u << 20)) __trap();
        if (tid_now() == 128) {
            m_load(sc, 0, par); m_load(sc, 1, par); m_load(sc, 2, par);
        }
    }
}
constexpr uint32_t kBarV = kSmemBase + kOffBar + 56;
__device__ __forceinline__ void v_load(const Scratch* sc, uint32_t par) {
    mbar_expect_tx(kBarV, kWBytes);
#pragma unroll 1
    for (int c = 0; c < 3; c++) bulk_load(kSmemBase + kOffWv + c * 24576, sc->img[par][1] + c * 1536, 24576, kBarV);
}
__device__ __forceinline__ void v_check(const Scratch* sc, uint32_t par) {
    for (uint32_t round = 0;; round++) {
        mbar_wait(kBarV, round & 1);
        uint32_t m = ~0u;
#pragma unroll
        for (int j = 0; j < 18; j++) {
            uint32_t v;
            asm volatile("ld.volatile.shared.b32 %0, [%1];" : "=r"(v)
                         : "r"(kSmemBase + kOffWv + 4096 * j + (tid_now() & 127) * 32 + (tid_now() & 28)) : "memory");
            m = min(m, v);
        }
        uint32_t all;
        asm volatile("{\n.reg .pred p, q;\nsetp.ne.u32 p, %1, 0;\nbar.red.and.pred q, 14, 128, p;\nselp.b32 %0, 1, 0, q;\n}\n" : "=r"(all) : "r"(m) : "memory");
        if (all) break;
        if (round > (1u << 20)) __trap();
        if (tid_now() == 352) v_load(sc, par);
    }
}
template <int K> struct Gemm1 {
    static __device__ __forceinline__ void run(float (&d)[96], uint32_t lx, uint32_t lw, bool very_first, uint32_t st) {
        if constexpr (K > 0) Gemm1<K - 1>::run(d, lx, lw, very_first, st);
        if constexpr (K == 0 || K == 4 || K == 8) {
            if (very_first) mbar_wait(bar_m(K / 4), (st & kRound) != 0);
            wg_fence();
        }
        wg192_ss<K == 0, koff(K, 8192), koff(K, 24576)>(d, lx, lw);
    }
};
constexpr uint32_t kScAddr = kSmemBase + kOffBar + 96;
__device__ __forceinline__ void draw_ticket(uint32_t& ticket) {
    asm volatile("{\n.reg .pred p;\n.reg .b64 a;\nsetp.eq.u32 p, %1, 0;\nld.volatile.shared.u64 a, [%3];\n"
                 "@p atom.relaxed.gpu.global.inc.u32 %0, [a + %4], %2;\n}\n"
                 : "+r"(ticket) : "r"(tid_now() & 127), "n"(kNWin - 1), "r"(kScAddr), "n"(offsetof(Scratch, ticket)) : "memory");
}
#define ALONE_COND (lnk == (tid_now() >> 7) + 8 && pub >= kNWin)
#define ALONE_V 4
#define G2_PASS 9
template <int KK> struct Gemm2 { static __device__ __forceinline__ void run(float (&d)[32], const uint32_t* a, uint32_t lx, uint32_t lnk, uint32_t& st) {
    Gemm2<KK - 1>::run(d, a, lx, lnk, st); wg64_rs<KK == 0, 0, koff(KK, 8192)>(d, a + 4 * KK, lx);
    if constexpr (KK == G2_PASS) {
        __syncwarp();
        bulk_wait_read();
        baton_pass(lnk, st);
    } } };
template <> struct Gemm2<-1> { static __device__ __forceinline__ void run(float (&)[32], const uint32_t*, uint32_t, uint32_t, uint32_t&) {} };
template <int KK> struct Gemm3 { static __device__ __forceinline__ void run(float (&d)[96], const uint32_t* a, uint32_t lxt) {
    Gemm3<KK - 1>::run(d, a, lxt); wg192_rs<KK == 0, 1, KK * (2048 >> 4)>(d, a + 4 * KK, lxt); } };
template <> struct Gemm3<-1> { static __device__ __forceinline__ void run(float (&)[96], const uint32_t*, uint32_t) {} };
template <int K0, int KK> struct Gemm4 { static __device__ __forceinline__ void run(float (&d)[96], const uint32_t* a, uint32_t lw) {
    if constexpr (KK > K0) Gemm4<K0, KK - 1>::run(d, a, lw);
    wg192_rs<KK == 0, 0, koff(KK, 24576)>(d, a + 4 * KK, lw); } };

template <int C, int KK> struct Gemm3s { static __device__ __forceinline__ void run(float (&d)[32], const uint32_t* a, uint32_t lxt, uint32_t one) {
    if constexpr (KK > 0) Gemm3s<C, KK - 1>::run(d, a, lxt, one);
    wg64_last<KK != 0, 1, (C * 8192 + KK * 2048) / 16>(d, a + 4 * KK, lxt, one * 0x40000040u, one); } };
template <int C, int K0, int KK> struct Gemm4s { static __device__ __forceinline__ void run(float (&d)[32], const uint32_t* a, uint32_t lw, uint32_t one) {
    if constexpr (KK > K0) Gemm4s<C, K0, KK - 1>::run(d, a, lw, one);
    wg64_last<KK == 0 ? 2 : 1, 0, koff(KK, 24576) + C * 8192 / 16>(d, a + 4 * KK, lw, one * 0x40000040u, one); } };

__device__ __forceinline__ uint32_t pack_bf16(float lo, float hi) {
    uint32_t r;
    asm("cvt.rn.bf16x2.f32 %0, %1, %2;" : "=r"(r) : "f"(hi), "f"(lo));
    return r;
}
__device__ __forceinline__ float ex2(float x) {
    float r;
    asm("ex2.approx.ftz.f32 %0, %1;" : "=f"(r) : "f"(x));
    return r;
}
__device__ __forceinline__ float rcp(float x) {
    float r;
    asm("rcp.approx.ftz.f32 %0, %1;" : "=f"(r) : "f"(x));
    return r;
}
__device__ __forceinline__ void mma16816(float (&c)[4], uint32_t a0, uint32_t a1, uint32_t a2, uint32_t a3,
                                         uint32_t b0, uint32_t b1) {
    asm volatile("mma.sync.aligned.m16n8k16.row.col.f32.bf16.bf16.f32 {%0,%1,%2,%3}, {%4,%5,%6,%7}, {%8,%9}, {%0,%1,%2,%3};"
                 : "+f"(c[0]), "+f"(c[1]), "+f"(c[2]), "+f"(c[3])
                 : "r"(a0), "r"(a1), "r"(a2), "r"(a3), "r"(b0), "r"(b1));
}

struct FoldRegs { uint4 B0[6], B1[6]; uint32_t A[48]; };

__device__ __forceinline__ void st_relaxed64(void* p, uint32_t a, uint32_t b, uint32_t on) {
    asm volatile("{\n.reg .pred q;\nsetp.ne.u32 q, %3, 0;\n@q st.relaxed.gpu.global.v2.b32 [%0], {%1, %2};\n}\n" ::"l"(p), "r"(a), "r"(b), "r"(on) : "memory");
}
__device__ __forceinline__ uint32_t pack_nonzero(float lo, float hi) { const uint32_t v = pack_bf16(lo, hi); return v != 0 ? v : 0x80000000u; }
__device__ __forceinline__ void fold_store(char* img, char* clear, uint32_t on, int n_lo, int n_hi, int k0, int q, const float (&c0)[4], const float (&c1)[4]) {
    const int u = ((k0 & 63) >> 3) + (q >> 1);
    const int base = (k0 >> 6) * 24576 + (q & 1) * 8;
    const int o_lo = base + n_lo * 128 + ((u ^ (n_lo & 7)) << 4), o_hi = base + n_hi * 128 + ((u ^ (n_hi & 7)) << 4);
    st_relaxed64(img + o_lo, pack_nonzero(c0[0], c0[1]), pack_nonzero(c1[0], c1[1]), on);
    st_relaxed64(img + o_hi, pack_nonzero(c0[2], c0[3]), pack_nonzero(c1[2], c1[3]), on);
    st_relaxed64(clear + o_lo, 0, 0, on);
    st_relaxed64(clear + o_hi, 0, 0, on);
}
__device__ __forceinline__ void fold_load_qk(FoldRegs& r, const __nv_bfloat16* __restrict__ wqkv, int tile, int lane) {
    const int g = lane >> 2, q = lane & 3;
    const int n0 = (tile / 12) * 16, k0 = (tile % 12) * 16;
    const int kb = k0 + 4 * (g >> 1) + (g & 1);
    const uint4* pa0 = reinterpret_cast<const uint4*>(wqkv + (size_t)(n0 + g) * 576 + 192 + 8 * q);
    const uint4* pa1 = reinterpret_cast<const uint4*>(wqkv + (size_t)(n0 + g + 8) * 576 + 192 + 8 * q);
    const uint4* pb0 = reinterpret_cast<const uint4*>(wqkv + (size_t)kb * 576 + 8 * q);
    const uint4* pb1 = reinterpret_cast<const uint4*>(wqkv + (size_t)(kb + 2) * 576 + 8 * q);
#pragma unroll
    for (int j = 0; j < 6; j++) {
        const uint4 lo = __ldg(pa0 + 4 * j), hi = __ldg(pa1 + 4 * j);
        r.A[8 * j + 0] = lo.x; r.A[8 * j + 1] = hi.x; r.A[8 * j + 2] = lo.y; r.A[8 * j + 3] = hi.y;
        r.A[8 * j + 4] = lo.z; r.A[8 * j + 5] = hi.z; r.A[8 * j + 6] = lo.w; r.A[8 * j + 7] = hi.w;
        r.B0[j] = __ldg(pb0 + 4 * j);
        r.B1[j] = __ldg(pb1 + 4 * j);
    }
}
__device__ __forceinline__ void fold_load_vo(FoldRegs& r, const __nv_bfloat16* __restrict__ wqkv, const __nv_bfloat16* __restrict__ wo,
                                             int tile, int lane) {
    const int g = lane >> 2, q = lane & 3;
    const int ch0 = (tile / 12) * 16 + 2 * g;
    const int k0 = (tile % 12) * 16;
    const int kb = k0 + 4 * (g >> 1) + (g & 1);
    const uint4* pb0 = reinterpret_cast<const uint4*>(wqkv + (size_t)kb * 576 + 384 + 8 * q);
    const uint4* pb1 = reinterpret_cast<const uint4*>(wqkv + (size_t)(kb + 2) * 576 + 384 + 8 * q);
    const uint32_t* pw = reinterpret_cast<const uint32_t*>(wo + (size_t)(8 * q) * kC + ch0);
#pragma unroll
    for (int j = 0; j < 6; j++) {
        r.B0[j] = __ldg(pb0 + 4 * j);
        r.B1[j] = __ldg(pb1 + 4 * j);
#pragma unroll
        for (int i = 0; i < 8; i++) r.A[8 * j + i] = __ldg(pw + (32 * j + i) * (kC / 2));
    }
}
template <bool kVO>
__device__ __forceinline__ void fold_compute_store(FoldRegs& r, Scratch* sc, int tile, int lane, uint32_t par, uint32_t on) {
    const int g = lane >> 2, q = lane & 3;
    float c0[4] = {0.f, 0.f, 0.f, 0.f}, c1[4] = {0.f, 0.f, 0.f, 0.f}, c2[4] = {0.f, 0.f, 0.f, 0.f}, c3[4] = {0.f, 0.f, 0.f, 0.f};
#pragma unroll
    for (int j = 0; j < 6; j++) {
        uint32_t a[8];
        if constexpr (kVO) {
#pragma unroll
            for (int i = 0; i < 4; i++) {
                a[2 * i]     = __byte_perm(r.A[8 * j + 2 * i], r.A[8 * j + 2 * i + 1], 0x5410);
                a[2 * i + 1] = __byte_perm(r.A[8 * j + 2 * i], r.A[8 * j + 2 * i + 1], 0x7632);
            }
        } else {
#pragma unroll
            for (int i = 0; i < 8; i++) a[i] = r.A[8 * j + i];
        }
        mma16816(c0, a[0], a[1], a[2], a[3], r.B0[j].x, r.B0[j].y);
        mma16816(c1, a[0], a[1], a[2], a[3], r.B1[j].x, r.B1[j].y);
        mma16816(c2, a[4], a[5], a[6], a[7], r.B0[j].z, r.B0[j].w);
        mma16816(c3, a[4], a[5], a[6], a[7], r.B1[j].z, r.B1[j].w);
    }
#pragma unroll
    for (int i = 0; i < 4; i++) { c0[i] += c2[i]; c1[i] += c3[i]; }
    const int k0 = (tile % 12) * 16;
    if constexpr (kVO) {
        const int n = (tile / 12) * 16 + 2 * g;
        fold_store(reinterpret_cast<char*>(sc->img[par][1]), reinterpret_cast<char*>(sc->img[par ^ 1][1]), on, n, n + 1, k0, q, c0, c1);
    } else {
        const int n0 = (tile / 12) * 16;
        fold_store(reinterpret_cast<char*>(sc->img[par][0]), reinterpret_cast<char*>(sc->img[par ^ 1][0]), on, n0 + g, n0 + g + 8, k0, q, c0, c1);
    }
}

__device__ __forceinline__ void prefetch_x(const CUtensorMap* tm, int win) {
    const int wh = win >> 6, ww = win & 63;
    asm volatile("cp.async.bulk.prefetch.tensor.3d.L2.global.tile [%0, {%1, %2, %3}];"
                 ::"l"(tm), "r"(0), "r"(ww * 8), "r"(wh * 8) : "memory");
}

__device__ __forceinline__ void reset_for_next_launch() {
    Scratch* q;
    asm volatile("ld.volatile.shared.u64 %0, [%1];" : "=l"(q) : "r"(kScAddr) : "memory");
    q->cnt_v[0] = 0; q->cnt_m[0] = 0; atomicAdd(q->epoch, 1);
}
__device__ __forceinline__ void finish_alone(uint32_t dXt, uint32_t dWv, [[maybe_unused]] const CUtensorMap* tm, int win) {
    uint32_t pa[16];
#pragma unroll
    for (int j = 0; j < 4; j++)
        asm volatile("ld.volatile.shared.v4.b32 {%0, %1, %2, %3}, [%4];" : "=r"(pa[4 * j]), "=r"(pa[4 * j + 1]), "=r"(pa[4 * j + 2]), "=r"(pa[4 * j + 3])
                     : "r"(kSmemBase + kOffStage + j * 2048 + (tid_now() & 127) * 16) : "memory");
    const uint32_t one = gridDim.y;
    float u0[32], u1[32], u2[32];
    float (&o0)[32] = u0, (&o1)[32] = u2, (&o2)[32] = u0;
    uint32_t fa[48];
    uint4 h[4];
    const float nz = __uint_as_float(one << 31);
    auto pack_a = [&](float (&u)[32], int c) {
        fence_regs(u);
#pragma unroll
        for (int i = 0; i < 16; i++) {
            fa[16 * c + i] = pack_bf16(c != 1 ? u[2 * i] + nz : u[2 * i], u[2 * i + 1]);
            asm volatile("" : "+r"(fa[16 * c + i])::"memory");
        }
        wg_fence();
    };
    auto pack_o = [&](float (&o)[32], [[maybe_unused]] bool first = false) {
        fence_regs(o);
        auto pk = [&](int i) { return pack_bf16(o[i], first ? o[i + 1] + nz : o[i + 1]); };
#pragma unroll
        for (int i = 0; i < 4; i++) {
            const int b = 16 * (i & 1) + 2 * (i >> 1);
            h[i] = make_uint4(pk(b), pk(b + 4), pk(b + 8), pk(b + 12));
        }
#pragma unroll
        for (int i = 0; i < 4; i++) asm volatile("" : "+r"(h[i].x), "+r"(h[i].y), "+r"(h[i].z), "+r"(h[i].w)::"memory");
    };
    TSTAMP(18);
    wg_fence();
    Gemm3s<0, 3>::run(u0, pa, dXt, one); wg_commit();
    TSTAMP(19);
    Gemm3s<1, 3>::run(u1, pa, dXt, one); wg_commit();
    Gemm3s<2, 3>::run(u2, pa, dXt, one); wg_commit();
    TSTAMP(20);
    const uint32_t t = tid_now(), slot = kSmemBase + kOffStage + (t & 96) * 64;
    const uint32_t sa = stage_addr(slot, t);
    const uint32_t tok = (t >> 3) & 3, j = t & 7, la = slot + tok * 128 + ((j ^ tok) << 4);
    char* out;
    asm volatile("ld.volatile.shared.u64 %0, [%1];" : "=l"(out) : "r"(kScAddr + 8) : "memory");
    out += (((win >> 6) * 8 + ((t >> 4) & 6)) * kHW + (win & 63) * 8 + tok) * (kC * 2) + j * 16;
    uint4 v[4];
    auto S = [&](int i, int off = 0) { stsm4((sa ^ (i & 1) * 64) + (i >> 1) * 1024 + off, h[i]); };
    auto L = [&](int i, int off = 0) {
        asm volatile("ld.volatile.shared.v4.b32 {%0, %1, %2, %3}, [%4];" : "=r"(v[i].x), "=r"(v[i].y), "=r"(v[i].z), "=r"(v[i].w)
                     : "r"((la ^ (i & 1) * 64) + i * 512 + off) : "memory");
    };
    auto G = [&](int c, int i) {
        asm volatile("st.global.v4.b32 [%0], {%1, %2, %3, %4};"
                     ::"l"(out + ((i >> 1) * kHW + 4 * (i & 1)) * (kC * 2) + c * 128), "r"(v[i].x), "r"(v[i].y), "r"(v[i].z), "r"(v[i].w) : "memory");
    };
#define W(C, K0, K1, O) Gemm4s<C, K0, K1>::run(O, fa, dWv, one)
#define PIN __syncwarp()
    wg_wait2(); TSTAMP(21); pack_a(u0, 0);
    asm volatile("bar.sync %0, 128;" ::"r"((tid_now() >> 7) + 1) : "memory");
    W(0, 0, 3, o0); wg_commit();
    wg_wait2(); TSTAMP(22); pack_a(u1, 1);
    W(0, 4, 7, o0); wg_commit();
    wg_wait2(); TSTAMP(23); pack_a(u2, 2);
    W(0, 8, 11, o0); wg_commit();
    W(1, 0, 5, o1); wg_commit();
    wg_wait1(); TSTAMP(24); pack_o(o0, true);
    W(1, 6, 6, o1); S(0); W(1, 7, 7, o1); S(1); W(1, 8, 8, o1); S(2); W(1, 9, 9, o1); S(3); W(1, 10, 10, o1); PIN; L(0); W(1, 11, 11, o1); wg_commit(); L(1);
    wg_fence();
    W(2, 0, 0, o2); L(2); W(2, 1, 1, o2); L(3); W(2, 2, 2, o2); PIN; G(0, 0); PIN; W(2, 3, 3, o2); G(0, 1); PIN; W(2, 4, 4, o2); G(0, 2); PIN; W(2, 5, 5, o2); wg_commit(); G(0, 3);
    PIN;
    wg_wait1(); TSTAMP(25); pack_o(o1);
    W(2, 6, 6, o2); S(0); W(2, 7, 7, o2); S(1); W(2, 8, 8, o2); S(2); W(2, 9, 9, o2); S(3); W(2, 10, 11, o2); wg_commit();
    wg_wait1();
    PIN; L(0); L(1); L(2); L(3); G(1, 0); G(1, 1); G(1, 2); G(1, 3);
    PIN;
    TSTAMP(26);
    wg_wait0(); TSTAMP(27); pack_o(o2);
    fence_regs(fa);
    S(0); S(1); S(2); S(3); PIN; L(0); L(1); L(2); L(3); G(2, 0); G(2, 1); G(2, 2); G(2, 3);
    TSTAMP(28);
#undef W
#undef PIN
}

__global__ void __launch_bounds__(kThreads, 1)
swin_attn_kernel(const __nv_bfloat16* __restrict__ wqkv, const __nv_bfloat16* __restrict__ wo, Scratch* __restrict__ sc, void* out,
                 const __grid_constant__ OutMaps tmo, const __grid_constant__ CUtensorMap tmx, const __grid_constant__ CUtensorMap tmp, const __grid_constant__ CUtensorMap tmc RT_ARG) {
    extern __shared__ uint8_t smem_raw[];
    constexpr uint32_t sbase = kSmemBase;
    if (smem_u32(smem_raw) != kSmemBase) __trap();
    const int tid = threadIdx.x, lane = tid & 31;
    const uint32_t warpu = __reduce_or_sync(0xffffffffu, (uint32_t)tid >> 5), wgu = warpu >> 2;
    const int warp = (int)warpu, wg = (int)wgu;
    const int G = gridDim.x;
    const uint32_t bar_full = sbase + kOffBar + 8 * wg;

    PROF(0); PROFG(1);
    if (wg == 0) FLOG(4096 + blockIdx.x * 4);
    const int ftile = blockIdx.x + (warp & 1) * G;
    FoldRegs fq;
#pragma unroll
    for (int j = 0; j < 6; j++) {
        asm volatile("" : "=r"(fq.B0[j].x), "=r"(fq.B0[j].y), "=r"(fq.B0[j].z), "=r"(fq.B0[j].w));
        asm volatile("" : "=r"(fq.B1[j].x), "=r"(fq.B1[j].y), "=r"(fq.B1[j].z), "=r"(fq.B1[j].w));
    }
#pragma unroll
    for (int j = 0; j < 48; j++) asm volatile("" : "=r"(fq.A[j]));
    if (warp < 2 && ftile < kTiles) fold_load_qk(fq, wqkv, ftile, lane);
    PSTAMP(0, 18);
    if (warp == 3) {
        const uint32_t i = blockIdx.x + G * (lane & 15);
        const char* p = lane < 16 ? (const char*)wo + i * 128 : (const char*)wqkv + i * 128 + (i / 3 + 1) * 768;
        if (i < 576) asm volatile("prefetch.global.L2 [%0];" ::"l"(p) : "memory");
    }
    uint32_t epoch;
    asm volatile("ld.relaxed.gpu.global.u32 %0, [%1];" : "=r"(epoch) : "l"(sc->epoch) : "memory");
    if (warp == 10) {
        if (lane == 0) {
#pragma unroll
            for (int w = 0; w < kNWG; w++) mbar_init(sbase + kOffBar + 8 * w, 1);
            asm volatile("fence.mbarrier_init.release.cluster;" ::: "memory");
        }
        __syncwarp();
        asm volatile("bar.arrive 11, 384;" ::: "memory");
        if (lane == 0) {
            const uint32_t t0 = (uint32_t)clock64() + TRK_START + ((blockIdx.x * 37) & 63) * TRK_STAG / 64;
#pragma unroll
            for (int w = 0; w < kNWG; w++) mbar_expect_tx(sbase + kOffBar + 8 * w, kXBytes);
            PSTAMP(320, 18);
#pragma unroll 1
            for (int i = 0; i < 3 * kNWG + (PF_INIT > 0); i++) {
                while ((int)((uint32_t)clock64() - t0) < (i < 3 ? i * TRK_STEP0 : TRK_MID + (i - 3) * TRK_STEP)) {}
                const int w = i / 3, c = i % 3;
                if (w < kNWG) tma_load_x_chunk(sbase + kOffX + w * kXBytes + c * 8192, &tmc, sbase + kOffBar + 8 * w, w * G + blockIdx.x, c);
                else prefetch_x(&tmp, kNWG * G + blockIdx.x);
            }
        }
    }
    if (warp < 3) {
        for (int t = ftile;;) {
            const bool on = warp < 2 && t < kTiles;
            fold_compute_store<false>(fq, sc, t, lane, epoch & 1, on);
            if (lane == 0 && on) asm volatile("red.relaxed.gpu.global.add.u32 [%0], %1;" ::"l"(sc->cnt_m), "r"(1u) : "memory");
            PSTAMP(0, 20); PSTAMP(32, 20);
            t += 2 * G;
            if (__builtin_expect(warp == 2 || t >= kTiles, 1)) break;
            fold_load_qk(fq, wqkv, t, lane);
        }
    }
    if (warp < 4) {
        asm volatile("bar.sync 11, 384;" ::: "memory");
    } else if (warp == 4) {
        if (lane == 0) {
            set_link(0, 9); set_link(1, 8); set_link(2, 8);
            asm volatile("st.shared.v2.u64 [%0], {%1, %2};" ::"r"(kScAddr), "l"(sc), "l"(out) : "memory");
            mbar_init(bar_m(0), 1);
            mbar_init(bar_m(1), 1);
            mbar_init(bar_m(2), 1);
            asm volatile("fence.mbarrier_init.release.cluster;" ::: "memory");
        }
        __syncwarp();
        asm volatile("bar.arrive 12, 128;" ::: "memory");
        asm volatile("bar.arrive 11, 384;" ::: "memory");
        if (lane == 0) {
            uint32_t v, spins = 0;
            do {
                asm volatile("ld.relaxed.gpu.global.u32 %0, [%1];" : "=r"(v) : "l"(sc->cnt_m) : "memory");
                if (++spins > (1u << 22)) __trap();
            } while (v < M_THR);
            PSTAMP(128, 21);
            const uint32_t par = epoch & 1;
            m_load(sc, 0, par); m_load(sc, 1, par); m_load(sc, 2, par);
            PSTAMP(128, 22);
        }
    } else if (warp == 11) {
        if (lane == 0) {
            mbar_init(kBarV, 1);
            asm volatile("fence.mbarrier_init.release.cluster;" ::: "memory");
        }
        __syncwarp();
        asm volatile("bar.sync 11, 384;" ::: "memory");
        if (lane == 0) {
            uint32_t v, spins = 0;
            do {
                asm volatile("ld.relaxed.gpu.global.u32 %0, [%1];" : "=r"(v) : "l"(sc->cnt_v) : "memory");
                if (++spins > (1u << 22)) __trap();
            } while (v < kTiles);
            PSTAMP(352, 23);
            { uint32_t ok = 0, n = 0;
              while (!ok && ++n < 64) asm volatile("{\n.reg .pred p;\nmbarrier.try_wait.parity.shared::cta.b64 p, [%1], 0;\nselp.b32 %0, 1, 0, p;\n}\n" : "=r"(ok) : "r"(bar_m(V_AFTER)) : "memory"); }
            v_load(sc, epoch & 1);
            PSTAMP(352, 24);
        }
    } else if (warp == 10) {
    } else if (warp >= 8) {
        asm volatile("bar.arrive 11, 384;" ::: "memory");
        if (VO_COND) { const uint32_t t0 = (uint32_t)clock64(); while ((uint32_t)clock64() - t0 < VO_DELAY) {} }
        FoldRegs fr;
        for (int t = G - 1 - blockIdx.x + (warp & 1) * G; t < kTiles; t += 2 * G) {
            const int tt = t;
            PSTAMP(256, 27);
            fold_load_vo(fr, wqkv, wo, tt, lane);
            PSTAMP(256, 28);
            fold_compute_store<true>(fr, sc, tt, lane, epoch & 1, 1);
            PSTAMP(256, 18);
            if (lane == 0) asm volatile("red.relaxed.gpu.global.add.u32 [%0], %1;" ::"l"(sc->cnt_v), "r"(1u) : "memory");
            PSTAMP(256, 19); PSTAMP(288, 19);
        }
    } else {
        asm volatile("bar.arrive 11, 384;" ::: "memory");
        if (lane == 0) asm volatile("prefetch.tensormap [%0];" ::"l"(warp == 5 ? &tmo.m[0] : warp == 6 ? &tmo.m[1] : &tmx) : "memory");
        asm volatile("bar.sync 12, 128;" ::: "memory");
    }
    __syncwarp();
    if (wg == 1) m_check(sc, epoch & 1);
    uint4 hv[12];
#pragma unroll
    for (int a = 0; a < 12; a++) asm volatile("" : "=r"(hv[a].x), "=r"(hv[a].y), "=r"(hv[a].z), "=r"(hv[a].w));

    constexpr uint32_t dWm = ((sbase + kOffWm) >> 4) | (1u << 16);
    constexpr uint32_t dWv = ((sbase + kOffWv) >> 4) | (1u << 16);
    const float cs = 0.07216878364870322f * 1.4426950408889634f;
    PROF(2);
    PSTAMP(0, 23);
    PROF(3);
    if (wg == 2) {
        asm volatile("bar.sync 13, 128;" ::: "memory");
        v_check(sc, epoch & 1);
        PSTAMP(256, 23);
    }
    mbar_wait(bar_full, 0);
    PSTAMP(0, 24); PSTAMP(128, 24); PSTAMP(256, 24);

    uint32_t st = (uint32_t)(wg * G + blockIdx.x) << 17 | kFirst | (wg == 0 ? kSolo | kVeryFirst : 0);

    while (true) {
        float acc[96];
        uint32_t fa[48];
        const uint32_t dX = ((sbase + kOffX + wg_uniform() * kXBytes) >> 4) | (1u << 16);
        uint32_t ticket = 0;
        STAMP(0);
        uint32_t lnk = baton_wait(st, 0);
        STAMP(1);
        while (true) {
            const bool very_first = st & kVeryFirst;
            Gemm1<11>::run(acc, dX, dWm, very_first, st);
            wg_commit();
            if (!very_first) { baton_pass(lnk, st); break; }
            wg_wait0();
            if (m_agree(1)) break;
            st ^= kRound;
        }
        STAMP(2);
        draw_ticket(ticket);
        if (!(st & kFirst)) {
            const uint32_t w4 = warp4_uniform();
            const uint32_t slot = sbase + kOffStage + w4 * 2048;
            const int col = (st_out(st) & 63) * 8, row = (st_out(st) >> 6) * 8 + 2 * w4;
            store_round<0>(hv, slot, tmo.m, col, row);
            bulk_wait_read();
            __syncwarp();
            store_round<1>(hv, slot, tmo.m, col, row);
            bulk_wait_read();
            __syncwarp();
            store_round<2>(hv, slot, tmo.m, col, row);
        }
        if ((st & kFirst) && (tid_now() == 128 || (PF_INIT > 2 && tid_now() == 256))) prefetch_x(&tmp, (kNWG + (tid_now() >> 7)) * gridDim.x + blockIdx.x);
        __syncwarp();
        wg_wait0();
        STAMP(3);
        fence_regs(acc);
#pragma unroll
        for (int i = 0; i < 48; i++) fa[i] = pack_bf16(acc[2 * i], acc[2 * i + 1]);

        float s[32];
        fence_regs(fa);
        STAMP(4);
        lnk = baton_wait(st, fa[47]);
        STAMP(5);
        wg_fence();
        Gemm2<11>::run(s, fa, dX, lnk, st);
        wg_commit();
        STAMP(6);
        wg_wait0();
        FLOG(st_win(st));
        STAMP(7);
        fence_regs(s);
        fence_regs(fa);

        uint32_t pa[16];
        {
            float a0[8], a1[8];
#pragma unroll
            for (int j = 0; j < 8; j++) { a0[j] = fmaxf(s[4 * j], s[4 * j + 1]); a1[j] = fmaxf(s[4 * j + 2], s[4 * j + 3]); }
#pragma unroll
            for (int d = 4; d > 0; d >>= 1)
#pragma unroll
                for (int j = 0; j < d; j++) { a0[j] = fmaxf(a0[j], a0[j + d]); a1[j] = fmaxf(a1[j], a1[j + d]); }
            float m0 = a0[0], m1 = a1[0];
            m0 = fmaxf(m0, __shfl_xor_sync(0xffffffffu, m0, 1));
            m1 = fmaxf(m1, __shfl_xor_sync(0xffffffffu, m1, 1));
            m0 = fmaxf(m0, __shfl_xor_sync(0xffffffffu, m0, 2));
            m1 = fmaxf(m1, __shfl_xor_sync(0xffffffffu, m1, 2));
            m0 *= cs; m1 *= cs;
            float l0 = 0.f, l1 = 0.f;
#pragma unroll
            for (int j = 0; j < 8; j++) {
                s[4 * j]     = ex2(fmaf(s[4 * j], cs, -m0));
                s[4 * j + 1] = ex2(fmaf(s[4 * j + 1], cs, -m0));
                s[4 * j + 2] = ex2(fmaf(s[4 * j + 2], cs, -m1));
                s[4 * j + 3] = ex2(fmaf(s[4 * j + 3], cs, -m1));
                l0 += s[4 * j] + s[4 * j + 1];
                l1 += s[4 * j + 2] + s[4 * j + 3];
            }
            l0 += __shfl_xor_sync(0xffffffffu, l0, 1);
            l1 += __shfl_xor_sync(0xffffffffu, l1, 1);
            l0 += __shfl_xor_sync(0xffffffffu, l0, 2);
            l1 += __shfl_xor_sync(0xffffffffu, l1, 2);
            const float r0 = rcp(l0), r1 = rcp(l1);
#pragma unroll
            for (int j = 0; j < 8; j++) {
                pa[2 * j]     = pack_bf16(s[4 * j] * r0, s[4 * j + 1] * r0);
                pa[2 * j + 1] = pack_bf16(s[4 * j + 2] * r1, s[4 * j + 3] * r1);
            }
        }

        fence_regs(pa);
        if ((tid_now() & 127) == 0)
            asm volatile("st.volatile.shared.u32 [%0], %1;" ::"r"(kLink + 4 + 8 * (tid_now() >> 7)), "r"(kNWG * gridDim.x + ticket) : "memory");
        STAMP(8);
        uint32_t pub;
        lnk = baton_wait_pub(st, pa[15], pub);
        if ((st & kFirst) && tid_now() == 0) set_link(1, 10);
        STAMP(9);
        const bool alone = ALONE_COND;
        asm volatile("{\n.reg .pred p;\nsetp.ne.u32 p, %16, 0;\n"
                     "@p st.volatile.shared.v4.b32 [%17], {%0, %1, %2, %3};\n@p st.volatile.shared.v4.b32 [%17 + 2048], {%4, %5, %6, %7};\n"
                     "@p st.volatile.shared.v4.b32 [%17 + 4096], {%8, %9, %10, %11};\n@p st.volatile.shared.v4.b32 [%17 + 6144], {%12, %13, %14, %15};\n}\n"
                     :: "r"(pa[0]), "r"(pa[1]), "r"(pa[2]), "r"(pa[3]), "r"(pa[4]), "r"(pa[5]), "r"(pa[6]), "r"(pa[7]),
                        "r"(pa[8]), "r"(pa[9]), "r"(pa[10]), "r"(pa[11]), "r"(pa[12]), "r"(pa[13]), "r"(pa[14]), "r"(pa[15]),
                        "r"((uint32_t)alone), "r"(sbase + kOffStage + (tid_now() & 127) * 16) : "memory");
        if (alone) {
            if (ticket == kNWin - 1) reset_for_next_launch();
            __syncwarp();
            finish_alone(dX + (((8192u >> 4) - 1) << 16), dWv, tmo.m, st_win(st));
            FLOG(4096 + blockIdx.x * 4 + 1 + (tid_now() >> 7));
            PROF(4); PROFG(5);
            return;
        }
        wg_fence();
        Gemm3<3>::run(acc, pa, dX + (((8192u >> 4) - 1) << 16));
        wg_commit();
        baton_pass(lnk, st);
        STAMP(10);
        const int nxt = (int)__reduce_or_sync(0xffffffffu, pub);
        auto prefetch_ahead = [&]() {
        if (((tid_now() >> 5) & 3) == 0 && nxt + PF_MIN < kNWin) {
            if (elect_one()) {
                const int base = kNWG * (int)gridDim.x, t = nxt - base;
                auto lead = [&](int tt) { return min(min(PF_INIT * (int)gridDim.x + ((tt * PF_UP) >> 8), PF_PEAK),
                                                     max(max(PF_PEAK - (((tt - PF_T1) * PF_D1) >> 8), PF_LEAD - ((tt * PF_DOWN) >> 8)), PF_MIN)); };
                const int hi = min(nxt + lead(t), kNWin - 1);
                int lo = max(max(nxt - 1 + lead(t - 1), nxt) + 1, base + PF_INIT * (int)gridDim.x);
#pragma unroll 1
                for (; lo <= hi; lo++) prefetch_x(&tmp, lo);
            }
            __syncwarp();
        }
        };
        wg_wait0();
        STAMP(11);
        fence_regs(acc);
        fence_regs(pa);

        if (((tid_now() >> 5) & 3) == 0 && nxt < kNWin) {
            asm volatile("bar.sync %0, 128;" ::"r"((tid_now() >> 7) + 1) : "memory");
            if (elect_one()) {
                const uint32_t wgl = tid_now() >> 7;
                const uint32_t bar = sbase + kOffBar + 8 * wgl;
                mbar_expect_tx(bar, kXBytes);
                tma_load_x(sbase + kOffX + wgl * kXBytes, &tmx, bar, nxt RT_EF);
            }
            __syncwarp();
        } else {
            asm volatile("bar.arrive %0, 128;" ::"r"((tid_now() >> 7) + 1) : "memory");
        }
#pragma unroll
        for (int i = 0; i < 48; i++) fa[i] = pack_bf16(acc[2 * i], acc[2 * i + 1]);

        asm volatile("st.volatile.shared.v4.b32 [%4], {%0, %1, %2, %3};"
                     :: "r"(fa[44]), "r"(fa[45]), "r"(fa[46]), "r"(fa[47]), "r"(sbase + kOffStash + (tid_now() & 127) * 16) : "memory");
        fence_regs(fa);
        prefetch_ahead();
        STAMP(12);
        lnk = baton_wait(st, fa[43]);
        STAMP(13);
        if (nxt >= kNWin) {
            if ((tid_now() & 127) == 0) {
#pragma unroll
                for (int w = 0; w < kNWG; w++) {
                    uint32_t l;
                    asm volatile("ld.volatile.shared.u32 %0, [%1];" : "=r"(l) : "r"(kLink + 8 * w) : "memory");
                    if (l == (tid_now() >> 7) + 8) set_link(w, lnk);
                }
            }
        }
        __syncwarp();
        wg_fence();
        Gemm4<0, 1>::run(acc, fa, dWv);
        wg_commit();
        Gemm4<2, 10>::run(acc, fa, dWv);
        wg_commit();
        wg_wait1();
        uint32_t fl[4];
        asm volatile("ld.volatile.shared.v4.b32 {%0, %1, %2, %3}, [%4];"
                     : "=r"(fl[0]), "=r"(fl[1]), "=r"(fl[2]), "=r"(fl[3]) : "r"(sbase + kOffStash + (tid_now() & 127) * 16) : "memory");
        wg_fence();
        wg192_rs<false, 0, koff(11, 24576)>(acc, fl, dWv);
        wg_commit();
        baton_pass(lnk, st);
        STAMP(14);
        if (nxt == kNWG * (int)gridDim.x + kNWin - 1 && (tid_now() & 127) == 0) reset_for_next_launch();
        __syncwarp();
        const int win_next = nxt;
        st = ((st ^ kPhase) & (kPhase | kSolo)) | st_win(st) << 4 | win_next << 17;
        uint32_t landed = 1;
        if (win_next < kNWin)
            asm volatile("{\n.reg .pred p;\nmbarrier.test_wait.parity.shared::cta.b64 p, [%1], %2;\nselp.b32 %0, 1, 0, p;\n}\n"
                         : "=r"(landed) : "r"(sbase + kOffBar + 8 * (tid_now() >> 7)), "r"(st & kPhase) : "memory");
        wg_wait0();
        STAMP(15);
        fence_regs(acc);
        fence_regs(fa);
        fence_regs(fl);

        {
#pragma unroll
            for (int a = 0; a < 6; a++) {
                hv[2 * a].x     = pack_bf16(acc[16 * a + 0], acc[16 * a + 1]);
                hv[2 * a].y     = pack_bf16(acc[16 * a + 4], acc[16 * a + 5]);
                hv[2 * a].z     = pack_bf16(acc[16 * a + 8], acc[16 * a + 9]);
                hv[2 * a].w     = pack_bf16(acc[16 * a + 12], acc[16 * a + 13]);
                hv[2 * a + 1].x = pack_bf16(acc[16 * a + 2], acc[16 * a + 3]);
                hv[2 * a + 1].y = pack_bf16(acc[16 * a + 6], acc[16 * a + 7]);
                hv[2 * a + 1].z = pack_bf16(acc[16 * a + 10], acc[16 * a + 11]);
                hv[2 * a + 1].w = pack_bf16(acc[16 * a + 14], acc[16 * a + 15]);
            }
        }
        STAMP(16);
        if (win_next >= kNWin) break;
        if (!landed) mbar_wait(sbase + kOffBar + 8 * (tid_now() >> 7), st & kPhase);
    }
    asm volatile("bar.sync %0, 128;" ::"r"((tid_now() >> 7) + 1) : "memory");
    {
        const uint32_t t = tid_opaque(), wu = __reduce_or_sync(0xffffffffu, t >> 5), w4 = wu & 3;
        const uint32_t slot = sbase + kOffX + wu * 6144, sa = stage_addr(slot, t);
        const int col = (st_out(st) & 63) * 8, row = (st_out(st) >> 6) * 8 + 2 * w4;
        stage_round<0>(hv, sa);
        stage_round<1>(hv, sa + 2048);
        stage_round<2>(hv, sa + 4096);
        stage_fence();
        send_round<0>(slot, tmo.m, col, row);
        send_round<1>(slot + 2048, tmo.m, col, row);
        send_round<2>(slot + 4096, tmo.m, col, row);
    }
    bulk_wait_read();
    FLOG(4096 + blockIdx.x * 4 + 1 + (tid_now() >> 7));
    PROF(4); PROFG(5);
    PROF_FLUSH();
}

typedef CUresult (*EncodeTiledFn)(CUtensorMap*, CUtensorMapDataType, cuuint32_t, void*, const cuuint64_t*,
                                  const cuuint64_t*, const cuuint32_t*, const cuuint32_t*, CUtensorMapInterleave,
                                  CUtensorMapSwizzle, CUtensorMapL2promotion, CUtensorMapFloatOOBfill);

}

extern "C" void kernel_launch(void* const* d_in, const int* in_sizes, int n_in, void* d_out, int out_size) {
    (void)in_sizes; (void)n_in; (void)out_size;
    const __nv_bfloat16* x    = (const __nv_bfloat16*)d_in[0];
    const __nv_bfloat16* wqkv = (const __nv_bfloat16*)d_in[1];
    const __nv_bfloat16* wo   = (const __nv_bfloat16*)d_in[2];

    static EncodeTiledFn encode = nullptr;
    static int num_sms = 0;
    static Scratch* scratch = nullptr;
    if (!encode) {
        void* fn = nullptr;
        cudaDriverEntryPointQueryResult qr;
        cudaGetDriverEntryPoint("cuTensorMapEncodeTiled", &fn, cudaEnableDefault, &qr);
        encode = (EncodeTiledFn)fn;
        cudaGetSymbolAddress((void**)&scratch, g_scratch);
        int dev = 0;
        cudaGetDevice(&dev);
        cudaDeviceGetAttribute(&num_sms, cudaDevAttrMultiProcessorCount, dev);
        cudaFuncSetAttribute(swin_attn_kernel, cudaFuncAttributeMaxDynamicSharedMemorySize, kSmemBytes);
    }
    CUtensorMap tmx;
    const cuuint64_t gdim[4] = {64, (cuuint64_t)kHW, (cuuint64_t)kHW, 3};
    const cuuint64_t gstr[3] = {(cuuint64_t)kC * 2, (cuuint64_t)kHW * kC * 2, 128};
    const cuuint32_t box[4] = {64, 8, 8, 3};
    const cuuint32_t estr[4] = {1, 1, 1, 1};
    encode(&tmx, CU_TENSOR_MAP_DATA_TYPE_BFLOAT16, 4, (void*)x, gdim, gstr, box, estr, CU_TENSOR_MAP_INTERLEAVE_NONE,
           CU_TENSOR_MAP_SWIZZLE_128B, CU_TENSOR_MAP_L2_PROMOTION_NONE, CU_TENSOR_MAP_FLOAT_OOB_FILL_NONE);

    CUtensorMap tmp;
    const cuuint64_t pdim[3] = {(cuuint64_t)kC, (cuuint64_t)kHW, (cuuint64_t)kHW};
    const cuuint64_t pstr[2] = {(cuuint64_t)kC * 2, (cuuint64_t)kHW * kC * 2};
    const cuuint32_t pbox[3] = {(cuuint32_t)kC, 8, 8};
    encode(&tmp, CU_TENSOR_MAP_DATA_TYPE_BFLOAT16, 3, (void*)x, pdim, pstr, pbox, estr, CU_TENSOR_MAP_INTERLEAVE_NONE,
           CU_TENSOR_MAP_SWIZZLE_NONE, CU_TENSOR_MAP_L2_PROMOTION_NONE, CU_TENSOR_MAP_FLOAT_OOB_FILL_NONE);
    CUtensorMap tmc;
    const cuuint32_t boxc[4] = {64, 8, 8, 1};
    encode(&tmc, CU_TENSOR_MAP_DATA_TYPE_BFLOAT16, 4, (void*)x, gdim, gstr, boxc, estr, CU_TENSOR_MAP_INTERLEAVE_NONE,
           CU_TENSOR_MAP_SWIZZLE_128B, CU_TENSOR_MAP_L2_PROMOTION_NONE, CU_TENSOR_MAP_FLOAT_OOB_FILL_NONE);
    OutMaps tmo;
    const cuuint32_t boxo[4] = {64, 8, 1, 2};
    encode(&tmo.m[0], CU_TENSOR_MAP_DATA_TYPE_BFLOAT16, 4, d_out, gdim, gstr, boxo, estr, CU_TENSOR_MAP_INTERLEAVE_NONE,
           CU_TENSOR_MAP_SWIZZLE_128B, CU_TENSOR_MAP_L2_PROMOTION_NONE, CU_TENSOR_MAP_FLOAT_OOB_FILL_NONE);
    const cuuint64_t odim[4] = {64, (cuuint64_t)kHW, (cuuint64_t)kHW, 2};
    const cuuint64_t ostr[3] = {(cuuint64_t)kC * 2, (cuuint64_t)kHW * kC * 2, (cuuint64_t)kHW * kC * 2 - 256};
    encode(&tmo.m[1], CU_TENSOR_MAP_DATA_TYPE_BFLOAT16, 4, (char*)d_out + 256, odim, ostr, boxo, estr, CU_TENSOR_MAP_INTERLEAVE_NONE,
           CU_TENSOR_MAP_SWIZZLE_128B, CU_TENSOR_MAP_L2_PROMOTION_NONE, CU_TENSOR_MAP_FLOAT_OOB_FILL_NONE);
    swin_attn_kernel<<<num_sms, kThreads, kSmemBytes, cudaStreamPerThread>>>(wqkv, wo, scratch, d_out, tmo, tmx, tmp, tmc
    );
}
```

```cpp
#include <cuda_runtime.h>
#include <cuda_bf16.h>
#include <cuda.h>
#include <stdint.h>

namespace {

constexpr int kC      = 192;
constexpr int kHW     = 512;
constexpr int kNWin   = 4096;
constexpr int kXBytes = 64 * kC * 2;
constexpr int kWBytes = kC * kC * 2;
constexpr int kNWG    = 3;
constexpr int kThreads = kNWG * 128;
constexpr int kTiles  = 144;
constexpr int kPfInit = 2, kPfUp = 160, kPfPeak = 400, kPfHold = 800, kPfDown1 = 40, kPfBase2 = 300, kPfDown2 = 12, kPfMin = 140;
__device__ __forceinline__ int pf_lead(int t) {
    return min(min(kPfInit * (int)gridDim.x + ((t * kPfUp) >> 8), kPfPeak),
               max(max(kPfPeak - (((t - kPfHold) * kPfDown1) >> 8), kPfBase2 - ((t * kPfDown2) >> 8)), kPfMin));
}
constexpr int kEvictFrom = 3100;
constexpr int kPaceStart = 100, kPaceSpread = 500, kPaceStep0 = 750, kPaceMid = 2400, kPaceStep = 500;
constexpr uint32_t kMqkHint = 100;
constexpr uint32_t kWvoDelay = 1000;

constexpr int kOffWm  = 0;
constexpr int kOffWv  = kWBytes;
constexpr int kOffX   = 2 * kWBytes;
constexpr int kOffStage = kOffX + kNWG * kXBytes;
constexpr int kOffStash = kOffStage + 8192;
constexpr int kOffBar = kOffStash + 2048;
constexpr int kSmemBytes = kOffBar + 128;
constexpr uint32_t kSmemBase = 1024;

struct Scratch {
    uint32_t ticket[32];
    uint32_t epoch[32];
    uint32_t cnt_v[32];
    uint32_t cnt_m[32];
    uint4 img[2][2][kWBytes / 16];
};
__device__ __align__(128) Scratch g_scratch;

__device__ __forceinline__ uint32_t smem_u32(const void* p) { return (uint32_t)__cvta_generic_to_shared(p); }

__device__ __forceinline__ void mbar_init(uint32_t bar, uint32_t count) {
    asm volatile("mbarrier.init.shared::cta.b64 [%0], %1;" ::"r"(bar), "r"(count) : "memory");
}
__device__ __forceinline__ void mbar_expect_tx(uint32_t bar, uint32_t bytes) {
    asm volatile("mbarrier.arrive.expect_tx.shared::cta.b64 _, [%0], %1;" ::"r"(bar), "r"(bytes) : "memory");
}
__device__ __forceinline__ void mbar_wait(uint32_t bar, uint32_t parity) {
    uint32_t ok;
    uint32_t spins = 0;
    do {
        asm volatile("{\n.reg .pred p;\n"
                     "mbarrier.try_wait.parity.shared::cta.b64 p, [%1], %2;\n"
                     "selp.b32 %0, 1, 0, p;\n}\n"
                     : "=r"(ok) : "r"(bar), "r"(parity) : "memory");
        if (++spins > (1u << 26)) __trap();
    } while (!ok);
}
__device__ __forceinline__ uint32_t tid_now() {
    uint32_t t;
    asm volatile("mov.u32 %0, %%tid.x;" : "=r"(t));
    return t;
}
__device__ __forceinline__ bool elect_one() {
    uint32_t pred;
    asm volatile("{\n.reg .pred p;\nelect.sync _|p, 0xffffffff;\nselp.b32 %0, 1, 0, p;\n}\n" : "=r"(pred));
    return pred != 0;
}
__device__ __forceinline__ uint32_t wg_uniform() { return __reduce_or_sync(0xffffffffu, tid_now() >> 7); }
constexpr uint32_t kLink = kSmemBase + kOffBar + 64;
constexpr uint32_t kPhase = 1;
constexpr uint32_t kSolo = 2;
constexpr uint32_t kFirst = 4;
constexpr uint32_t kRound = 8;
constexpr uint32_t kVeryFirst = 1u << 16;
__device__ __forceinline__ int st_out(uint32_t st) { return (st >> 4) & 0xfff; }
__device__ __forceinline__ int st_win(uint32_t st) { return st >> 17; }
__device__ __forceinline__ uint32_t baton_wait(uint32_t st, uint32_t packed) {
    if (packed == 0xffffffffu) __trap();
    if (!(st & kSolo)) asm volatile("bar.sync %0, 256;" ::"r"((tid_now() >> 7) + 8) : "memory");
    uint32_t lnk;
    asm volatile("ld.volatile.shared.u32 %0, [%1];" : "=r"(lnk) : "r"(kLink + 8 * (tid_now() >> 7)) : "memory");
    return lnk;
}
__device__ __forceinline__ uint32_t baton_wait_pub(uint32_t st, uint32_t packed, uint32_t& pub) {
    if (packed == 0xffffffffu) __trap();
    asm volatile("bar.sync %0, %1;" ::"r"((tid_now() >> 7) + 8), "r"(st & kSolo ? 128 : 256) : "memory");
    uint32_t lnk;
    asm volatile("ld.volatile.shared.v2.u32 {%0, %1}, [%2];" : "=r"(lnk), "=r"(pub) : "r"(kLink + 8 * (tid_now() >> 7)) : "memory");
    return lnk;
}
__device__ __forceinline__ void baton_pass(uint32_t lnk, uint32_t& st) {
    const bool other = lnk != (tid_now() >> 7) + 8;
    if (other) asm volatile("bar.arrive %0, 256;" ::"r"(lnk) : "memory");
    st = other ? st & ~kSolo : st | kSolo;
}
__device__ __forceinline__ void set_link(int w, uint32_t v) { asm volatile("st.volatile.shared.u32 [%0], %1;" ::"r"(kLink + 8 * w), "r"(v) : "memory"); }
constexpr uint64_t kPolNormal = 0x1000000000000000ull, kPolFirst = 0x12F0000000000000ull;
__device__ __forceinline__ void tma_load_x(uint32_t dst, const CUtensorMap* tm, uint32_t bar, int win) {
    const int wh = win >> 6, ww = win & 63;
    asm volatile("cp.async.bulk.tensor.4d.shared::cluster.global.mbarrier::complete_tx::bytes.L2::cache_hint"
                 " [%0], [%1, {%3, %4, %5, %6}], [%2], %7;"
                 ::"r"(dst), "l"(tm), "r"(bar), "r"(0), "r"(ww * 8), "r"(wh * 8), "r"(0), "l"(win >= kEvictFrom ? kPolFirst : kPolNormal) : "memory");
}
__device__ __forceinline__ void tma_load_x_chunk(uint32_t dst, const CUtensorMap* tm, uint32_t bar, int win, int chunk) {
    const int wh = win >> 6, ww = win & 63;
    asm volatile("cp.async.bulk.tensor.4d.shared::cluster.global.mbarrier::complete_tx::bytes"
                 " [%0], [%1, {%3, %4, %5, %6}], [%2];"
                 ::"r"(dst), "l"(tm), "r"(bar), "r"(0), "r"(ww * 8), "r"(wh * 8), "r"(chunk) : "memory");
}
__device__ __forceinline__ void bulk_load(uint32_t dst, const void* src, uint32_t bytes, uint32_t bar) {
    asm volatile("cp.async.bulk.shared::cluster.global.mbarrier::complete_tx::bytes [%0], [%1], %2, [%3];"
                 ::"r"(dst), "l"(src), "r"(bytes), "r"(bar) : "memory");
}

__device__ __forceinline__ void wg_fence()  { asm volatile("wgmma.fence.sync.aligned;" ::: "memory"); }
__device__ __forceinline__ void wg_commit() { asm volatile("wgmma.commit_group.sync.aligned;" ::: "memory"); }
__device__ __forceinline__ void wg_wait0()  { asm volatile("wgmma.wait_group.sync.aligned 0;" ::: "memory"); }
__device__ __forceinline__ void wg_wait1()  { asm volatile("wgmma.wait_group.sync.aligned 1;" ::: "memory"); }
__device__ __forceinline__ void wg_wait2()  { asm volatile("wgmma.wait_group.sync.aligned 2;" ::: "memory"); }

template <int N> __device__ __forceinline__ void fence_regs(float (&d)[N]) {
#pragma unroll
    for (int i = 0; i < N; i++) asm volatile("" : "+f"(d[i])::"memory");
}
template <int N> __device__ __forceinline__ void fence_regs(uint32_t (&d)[N]) {
#pragma unroll
    for (int i = 0; i < N; i++) asm volatile("" : "+r"(d[i])::"memory");
}

#define ACC8(c, d, i) c(d[i]), c(d[i + 1]), c(d[i + 2]), c(d[i + 3]), c(d[i + 4]), c(d[i + 5]), c(d[i + 6]), c(d[i + 7])
#define ACC32(c, d) ACC8(c, d, 0), ACC8(c, d, 8), ACC8(c, d, 16), ACC8(c, d, 24)
#define ACC96(c, d) ACC32(c, d), ACC8(c, d, 32), ACC8(c, d, 40), ACC8(c, d, 48), ACC8(c, d, 56), \
                    ACC8(c, d, 64), ACC8(c, d, 72), ACC8(c, d, 80), ACC8(c, d, 88)
#define C_IO(x) "+f"(x)
#define C_O(x) "=f"(x)
#define REGS32 "{%0, %1, %2, %3, %4, %5, %6, %7, %8, %9, %10, %11, %12, %13, %14, %15, " \
               "%16, %17, %18, %19, %20, %21, %22, %23, %24, %25, %26, %27, %28, %29, %30, %31}"
#define REGS96 "{%0, %1, %2, %3, %4, %5, %6, %7, %8, %9, %10, %11, %12, %13, %14, %15, " \
               "%16, %17, %18, %19, %20, %21, %22, %23, %24, %25, %26, %27, %28, %29, %30, %31, " \
               "%32, %33, %34, %35, %36, %37, %38, %39, %40, %41, %42, %43, %44, %45, %46, %47, " \
               "%48, %49, %50, %51, %52, %53, %54, %55, %56, %57, %58, %59, %60, %61, %62, %63, " \
               "%64, %65, %66, %67, %68, %69, %70, %71, %72, %73, %74, %75, %76, %77, %78, %79, " \
               "%80, %81, %82, %83, %84, %85, %86, %87, %88, %89, %90, %91, %92, %93, %94, %95}"

#define DESC_HI "0x40000040"
#define MK_DESC(name, lo, off) "add.u32 t, " lo ", " off ";\nmov.b64 " name ", {t, " DESC_HI "};\n"

template <bool First, int OA, int OB> __device__ __forceinline__ void wg192_ss(float (&d)[96], uint32_t la, uint32_t lb) {
    if constexpr (First)
        asm volatile("{\n.reg .pred p;\n.reg .b32 t;\n.reg .b64 da, db;\nsetp.ne.b32 p, 0, 0;\n"
                     MK_DESC("da", "%96", "%98") MK_DESC("db", "%97", "%99")
                     "wgmma.mma_async.sync.aligned.m64n192k16.f32.bf16.bf16 " REGS96 ", da, db, p, 1, 1, 0, 0;\n}\n"
                     : ACC96(C_O, d) : "r"(la), "r"(lb), "n"(OA), "n"(OB));
    else
        asm volatile("{\n.reg .pred p;\n.reg .b32 t;\n.reg .b64 da, db;\nsetp.ne.b32 p, 1, 0;\n"
                     MK_DESC("da", "%96", "%98") MK_DESC("db", "%97", "%99")
                     "wgmma.mma_async.sync.aligned.m64n192k16.f32.bf16.bf16 " REGS96 ", da, db, p, 1, 1, 0, 0;\n}\n"
                     : ACC96(C_IO, d) : "r"(la), "r"(lb), "n"(OA), "n"(OB));
}
template <bool First, int TB, int OB> __device__ __forceinline__ void wg192_rs(float (&d)[96], const uint32_t* a, uint32_t lb) {
    if constexpr (First)
        asm volatile("{\n.reg .pred p;\n.reg .b32 t;\n.reg .b64 db;\nsetp.ne.b32 p, 0, 0;\n"
                     MK_DESC("db", "%100", "%102")
                     "wgmma.mma_async.sync.aligned.m64n192k16.f32.bf16.bf16 " REGS96 ", {%96, %97, %98, %99}, db, p, 1, 1, %101;\n}\n"
                     : ACC96(C_O, d) : "r"(a[0]), "r"(a[1]), "r"(a[2]), "r"(a[3]), "r"(lb), "n"(TB), "n"(OB));
    else
        asm volatile("{\n.reg .pred p;\n.reg .b32 t;\n.reg .b64 db;\nsetp.ne.b32 p, 1, 0;\n"
                     MK_DESC("db", "%100", "%102")
                     "wgmma.mma_async.sync.aligned.m64n192k16.f32.bf16.bf16 " REGS96 ", {%96, %97, %98, %99}, db, p, 1, 1, %101;\n}\n"
                     : ACC96(C_IO, d) : "r"(a[0]), "r"(a[1]), "r"(a[2]), "r"(a[3]), "r"(lb), "n"(TB), "n"(OB));
}
template <bool First, int TB, int OB> __device__ __forceinline__ void wg64_rs(float (&d)[32], const uint32_t* a, uint32_t lb) {
    if constexpr (First)
        asm volatile("{\n.reg .pred p;\n.reg .b32 t;\n.reg .b64 db;\nsetp.ne.b32 p, 0, 0;\n"
                     MK_DESC("db", "%36", "%38")
                     "wgmma.mma_async.sync.aligned.m64n64k16.f32.bf16.bf16 " REGS32 ", {%32, %33, %34, %35}, db, p, 1, 1, %37;\n}\n"
                     : ACC32(C_O, d) : "r"(a[0]), "r"(a[1]), "r"(a[2]), "r"(a[3]), "r"(lb), "n"(TB), "n"(OB));
    else
        asm volatile("{\n.reg .pred p;\n.reg .b32 t;\n.reg .b64 db;\nsetp.ne.b32 p, 1, 0;\n"
                     MK_DESC("db", "%36", "%38")
                     "wgmma.mma_async.sync.aligned.m64n64k16.f32.bf16.bf16 " REGS32 ", {%32, %33, %34, %35}, db, p, 1, 1, %37;\n}\n"
                     : ACC32(C_IO, d) : "r"(a[0]), "r"(a[1]), "r"(a[2]), "r"(a[3]), "r"(lb), "n"(TB), "n"(OB));
}
template <int OB> __device__ __forceinline__ void wg64_rs_reuse(float (&d)[32], const uint32_t* a, uint32_t lb, uint32_t one) {
    asm volatile("{\n.reg .pred p;\n.reg .b32 t;\n.reg .b64 db;\nsetp.ne.b32 p, %38, 1;\n"
                 MK_DESC("db", "%36", "%37")
                 "wgmma.mma_async.sync.aligned.m64n64k16.f32.bf16.bf16 " REGS32 ", {%32, %33, %34, %35}, db, p, 1, 1, 0;\n}\n"
                 : ACC32(C_IO, d) : "r"(a[0]), "r"(a[1]), "r"(a[2]), "r"(a[3]), "r"(lb), "n"(OB), "r"(one));
}
__host__ __device__ constexpr int koff(int kk, int chunk) { return ((kk >> 2) * chunk + (kk & 3) * 32) >> 4; }

__device__ __forceinline__ void stsm4(uint32_t addr, const uint4& v) {
    asm volatile("stmatrix.sync.aligned.m8n8.x4.shared.b16 [%0], {%1, %2, %3, %4};" ::"r"(addr), "r"(v.x), "r"(v.y), "r"(v.z), "r"(v.w) : "memory");
}
__device__ __forceinline__ void bulk_wait_read() {
    asm volatile("cp.async.bulk.wait_group.read 0;" ::: "memory");
}
__device__ __forceinline__ uint32_t stage_addr(uint32_t slot, uint32_t l) { return slot + (l & 7) * 128 + ((((l >> 3) & 3) ^ (l & 7)) << 4); }
__device__ __forceinline__ uint32_t tid_opaque() { return __shfl_sync(0xffffffffu, tid_now(), tid_now() & 31); }
template <int R> __device__ __forceinline__ void stage_round(const uint4 (&h)[12], uint32_t sa) {
#pragma unroll
    for (int i = 0; i < 2; i++) {
        const int r = (2 * R + i) / 3, c = (2 * R + i) % 3;
        stsm4(sa + i * 1024, h[4 * c + r]);
        stsm4((sa ^ 64) + i * 1024, h[4 * c + 2 + r]);
    }
}
__device__ __forceinline__ void stage_fence() {
    asm volatile("fence.proxy.async.shared::cta;" ::: "memory");
    __syncwarp();
}
template <int R> __device__ __forceinline__ void send_round(uint32_t slot, const CUtensorMap* tm, int col, int row) {
    asm volatile("{\n.reg .pred p;\nelect.sync _|p, 0xffffffff;\n"
                 "@p cp.async.bulk.tensor.4d.global.shared::cta.bulk_group [%0, {%2, %3, %4, %5}], [%1];\n"
                 "@p cp.async.bulk.commit_group;\n}\n"
                 ::"l"(tm + (R == 1)), "r"(slot), "r"(0), "r"(col), "r"(row + (R == 2)), "r"((int)(R == 2)) : "memory");
}
template <int R> __device__ __forceinline__ void store_round(const uint4 (&h)[12], uint32_t slot, const CUtensorMap* tm, int col, int row) {
    stage_round<R>(h, stage_addr(slot, tid_now()));
    stage_fence();
    send_round<R>(slot, tm, col, row);
}
__device__ __forceinline__ uint32_t warp4_uniform() { return __reduce_or_sync(0xffffffffu, (tid_now() >> 5) & 3); }
struct OutMaps { CUtensorMap m[2]; };
__host__ __device__ constexpr uint32_t bar_m(int c) { return kSmemBase + kOffBar + 32 + 8 * c; }
__device__ __forceinline__ void m_load(const Scratch* sc, int c, uint32_t par) {
    mbar_expect_tx(bar_m(c), 24576);
    bulk_load(kSmemBase + kOffWm + c * 24576, sc->img[par][0] + c * 1536, 24576, bar_m(c));
}
__device__ __forceinline__ bool m_agree(uint32_t ok) {
    uint32_t all;
    asm volatile("{\n.reg .pred p, q;\nsetp.ne.u32 p, %1, 0;\nbar.red.and.pred q, 7, 256, p;\nselp.b32 %0, 1, 0, q;\n}\n" : "=r"(all) : "r"(ok) : "memory");
    return all != 0;
}
__device__ __forceinline__ void m_check(const Scratch* sc, uint32_t par) {
    for (uint32_t round = 0;; round++) {
        uint32_t m = ~0u;
#pragma unroll 1
        for (int c = 0; c < 3; c++) {
            mbar_wait(bar_m(c), round & 1);
#pragma unroll
            for (int j = 0; j < 6; j++) {
                uint32_t v;
                asm volatile("ld.volatile.shared.b32 %0, [%1];" : "=r"(v)
                             : "r"(kSmemBase + kOffWm + c * 24576 + 4096 * j + (tid_now() & 127) * 32 + (tid_now() & 28)) : "memory");
                m = min(m, v);
            }
        }
        if (m_agree(m)) break;
        if (round > (1u << 20)) __trap();
        if (tid_now() == 128) {
            m_load(sc, 0, par); m_load(sc, 1, par); m_load(sc, 2, par);
        }
    }
}
constexpr uint32_t kBarV = kSmemBase + kOffBar + 56;
__device__ __forceinline__ void v_load(const Scratch* sc, uint32_t par) {
    mbar_expect_tx(kBarV, kWBytes);
#pragma unroll 1
    for (int c = 0; c < 3; c++) bulk_load(kSmemBase + kOffWv + c * 24576, sc->img[par][1] + c * 1536, 24576, kBarV);
}
__device__ __forceinline__ void v_check(const Scratch* sc, uint32_t par) {
    for (uint32_t round = 0;; round++) {
        mbar_wait(kBarV, round & 1);
        uint32_t m = ~0u;
#pragma unroll
        for (int j = 0; j < 18; j++) {
            uint32_t v;
            asm volatile("ld.volatile.shared.b32 %0, [%1];" : "=r"(v)
                         : "r"(kSmemBase + kOffWv + 4096 * j + (tid_now() & 127) * 32 + (tid_now() & 28)) : "memory");
            m = min(m, v);
        }
        uint32_t all;
        asm volatile("{\n.reg .pred p, q;\nsetp.ne.u32 p, %1, 0;\nbar.red.and.pred q, 14, 128, p;\nselp.b32 %0, 1, 0, q;\n}\n" : "=r"(all) : "r"(m) : "memory");
        if (all) break;
        if (round > (1u << 20)) __trap();
        if (tid_now() == 352) v_load(sc, par);
    }
}
template <int K> struct Gemm1 {
    static __device__ __forceinline__ void run(float (&d)[96], uint32_t lx, uint32_t lw, bool very_first, uint32_t st) {
        if constexpr (K > 0) Gemm1<K - 1>::run(d, lx, lw, very_first, st);
        if constexpr (K == 0 || K == 4 || K == 8) {
            if (very_first) mbar_wait(bar_m(K / 4), (st & kRound) != 0);
            wg_fence();
        }
        wg192_ss<K == 0, koff(K, 8192), koff(K, 24576)>(d, lx, lw);
    }
};
constexpr uint32_t kScAddr = kSmemBase + kOffBar + 96;
__device__ __forceinline__ void draw_ticket(uint32_t& ticket) {
    asm volatile("{\n.reg .pred p;\n.reg .b64 a;\nsetp.eq.u32 p, %1, 0;\nld.volatile.shared.u64 a, [%3];\n"
                 "@p atom.relaxed.gpu.global.inc.u32 %0, [a], %2;\n}\n"
                 : "+r"(ticket) : "r"(tid_now() & 127), "n"(kNWin - 1), "r"(kScAddr) : "memory");
}
template <int KK> struct Gemm2 { static __device__ __forceinline__ void run(float (&d)[32], const uint32_t* a, uint32_t lx, uint32_t lnk, uint32_t& st) {
    Gemm2<KK - 1>::run(d, a, lx, lnk, st); wg64_rs<KK == 0, 0, koff(KK, 8192)>(d, a + 4 * KK, lx);
    if constexpr (KK == 9) {
        __syncwarp();
        bulk_wait_read();
        baton_pass(lnk, st);
    } } };
template <> struct Gemm2<-1> { static __device__ __forceinline__ void run(float (&)[32], const uint32_t*, uint32_t, uint32_t, uint32_t&) {} };
template <int KK> struct Gemm3 { static __device__ __forceinline__ void run(float (&d)[96], const uint32_t* a, uint32_t lxt) {
    Gemm3<KK - 1>::run(d, a, lxt); wg192_rs<KK == 0, 1, KK * (2048 >> 4)>(d, a + 4 * KK, lxt); } };
template <> struct Gemm3<-1> { static __device__ __forceinline__ void run(float (&)[96], const uint32_t*, uint32_t) {} };
template <int K0, int KK> struct Gemm4 { static __device__ __forceinline__ void run(float (&d)[96], const uint32_t* a, uint32_t lw) {
    if constexpr (KK > K0) Gemm4<K0, KK - 1>::run(d, a, lw);
    wg192_rs<KK == 0, 0, koff(KK, 24576)>(d, a + 4 * KK, lw); } };

template <int C, int KK> struct Gemm3s { static __device__ __forceinline__ void run(float (&d)[32], const uint32_t* a, uint32_t lxt) {
    if constexpr (KK > 0) Gemm3s<C, KK - 1>::run(d, a, lxt);
    wg64_rs<KK == 0, 1, (C * 8192 + KK * 2048) / 16>(d, a + 4 * KK, lxt); } };
template <int C, int K0, int KK> struct Gemm4s { static __device__ __forceinline__ void run(float (&d)[32], const uint32_t* a, uint32_t lw, uint32_t one) {
    if constexpr (KK > K0) Gemm4s<C, K0, KK - 1>::run(d, a, lw, one);
    if constexpr (KK == 0) wg64_rs_reuse<C * 8192 / 16>(d, a, lw, one);
    else wg64_rs<false, 0, koff(KK, 24576) + C * 8192 / 16>(d, a + 4 * KK, lw); } };

__device__ __forceinline__ uint32_t pack_bf16(float lo, float hi) {
    uint32_t r;
    asm("cvt.rn.bf16x2.f32 %0, %1, %2;" : "=r"(r) : "f"(hi), "f"(lo));
    return r;
}
__device__ __forceinline__ float ex2(float x) {
    float r;
    asm("ex2.approx.ftz.f32 %0, %1;" : "=f"(r) : "f"(x));
    return r;
}
__device__ __forceinline__ float rcp(float x) {
    float r;
    asm("rcp.approx.ftz.f32 %0, %1;" : "=f"(r) : "f"(x));
    return r;
}
__device__ __forceinline__ void mma16816(float (&c)[4], uint32_t a0, uint32_t a1, uint32_t a2, uint32_t a3,
                                         uint32_t b0, uint32_t b1) {
    asm volatile("mma.sync.aligned.m16n8k16.row.col.f32.bf16.bf16.f32 {%0,%1,%2,%3}, {%4,%5,%6,%7}, {%8,%9}, {%0,%1,%2,%3};"
                 : "+f"(c[0]), "+f"(c[1]), "+f"(c[2]), "+f"(c[3])
                 : "r"(a0), "r"(a1), "r"(a2), "r"(a3), "r"(b0), "r"(b1));
}

struct FoldRegs { uint4 B0[6], B1[6]; uint32_t A[48]; };

__device__ __forceinline__ void st_relaxed64(void* p, uint32_t a, uint32_t b, uint32_t on) {
    asm volatile("{\n.reg .pred q;\nsetp.ne.u32 q, %3, 0;\n@q st.relaxed.gpu.global.v2.b32 [%0], {%1, %2};\n}\n" ::"l"(p), "r"(a), "r"(b), "r"(on) : "memory");
}
__device__ __forceinline__ uint32_t pack_nonzero(float lo, float hi) { const uint32_t v = pack_bf16(lo, hi); return v != 0 ? v : 0x80000000u; }
__device__ __forceinline__ void fold_store(char* img, uint32_t* cnt, uint32_t epoch, uint32_t on, int n_lo, int n_hi, int k0, int lane, const float (&c0)[4], const float (&c1)[4]) {
    const int q = lane & 3;
    const int u = ((k0 & 63) >> 3) + (q >> 1);
    const int base = (k0 >> 6) * 24576 + (q & 1) * 8;
    char* p_lo = img + (base + n_lo * 128 + ((u ^ (n_lo & 7)) << 4));
    char* p_hi = img + (base + n_hi * 128 + ((u ^ (n_hi & 7)) << 4));
    const uint32_t v0 = pack_nonzero(c0[0], c0[1]);
    const uint32_t par = (epoch & 1) | (v0 & (gridDim.y - 1));
    st_relaxed64(p_lo + par * (2 * kWBytes), v0, pack_nonzero(c1[0], c1[1]), on);
    st_relaxed64(p_hi + par * (2 * kWBytes), pack_nonzero(c0[2], c0[3]), pack_nonzero(c1[2], c1[3]), on);
    asm volatile("{\n.reg .pred q;\nsetp.ne.u32 q, %1, 0;\n@q red.relaxed.gpu.global.inc.u32 [%0], 0xffffffff;\n}\n" ::"l"(cnt), "r"(lane == 0 ? on : 0u) : "memory");
    st_relaxed64(p_lo + (par ^ 1) * (2 * kWBytes), 0, 0, on);
    st_relaxed64(p_hi + (par ^ 1) * (2 * kWBytes), 0, 0, on);
}
__device__ __forceinline__ void fold_load_qk(FoldRegs& r, const __nv_bfloat16* __restrict__ wqkv, int tile, int lane) {
    const int g = lane >> 2, q = lane & 3;
    const int n0 = (tile / 12) * 16, k0 = (tile % 12) * 16;
    const int kb = k0 + 4 * (g >> 1) + (g & 1);
    const uint4* pa0 = reinterpret_cast<const uint4*>(wqkv + (size_t)(n0 + g) * 576 + 192 + 8 * q);
    const uint4* pa1 = reinterpret_cast<const uint4*>(wqkv + (size_t)(n0 + g + 8) * 576 + 192 + 8 * q);
    const uint4* pb0 = reinterpret_cast<const uint4*>(wqkv + (size_t)kb * 576 + 8 * q);
    const uint4* pb1 = reinterpret_cast<const uint4*>(wqkv + (size_t)(kb + 2) * 576 + 8 * q);
#pragma unroll
    for (int j = 0; j < 6; j++) {
        const uint4 lo = __ldg(pa0 + 4 * j), hi = __ldg(pa1 + 4 * j);
        r.A[8 * j + 0] = lo.x; r.A[8 * j + 1] = hi.x; r.A[8 * j + 2] = lo.y; r.A[8 * j + 3] = hi.y;
        r.A[8 * j + 4] = lo.z; r.A[8 * j + 5] = hi.z; r.A[8 * j + 6] = lo.w; r.A[8 * j + 7] = hi.w;
        r.B0[j] = __ldg(pb0 + 4 * j);
        r.B1[j] = __ldg(pb1 + 4 * j);
    }
}
__device__ __forceinline__ void fold_load_vo(FoldRegs& r, const __nv_bfloat16* __restrict__ wqkv, const __nv_bfloat16* __restrict__ wo,
                                             int tile, int lane) {
    const int g = lane >> 2, q = lane & 3;
    const int ch0 = (tile / 12) * 16 + 2 * g;
    const int k0 = (tile % 12) * 16;
    const int kb = k0 + 4 * (g >> 1) + (g & 1);
    const uint4* pb0 = reinterpret_cast<const uint4*>(wqkv + (size_t)kb * 576 + 384 + 8 * q);
    const uint4* pb1 = reinterpret_cast<const uint4*>(wqkv + (size_t)(kb + 2) * 576 + 384 + 8 * q);
    const uint32_t* pw = reinterpret_cast<const uint32_t*>(wo + (size_t)(8 * q) * kC + ch0);
#pragma unroll
    for (int j = 0; j < 6; j++) {
        r.B0[j] = __ldg(pb0 + 4 * j);
        r.B1[j] = __ldg(pb1 + 4 * j);
#pragma unroll
        for (int i = 0; i < 8; i++) r.A[8 * j + i] = __ldg(pw + (32 * j + i) * (kC / 2));
    }
}
template <bool kVO>
__device__ __forceinline__ void fold_compute_store(FoldRegs& r, Scratch* sc, int tile, int lane, uint32_t epoch, uint32_t on) {
    const int g = lane >> 2;
    float c0[4] = {0.f, 0.f, 0.f, 0.f}, c1[4] = {0.f, 0.f, 0.f, 0.f}, c2[4] = {0.f, 0.f, 0.f, 0.f}, c3[4] = {0.f, 0.f, 0.f, 0.f};
#pragma unroll
    for (int j = 0; j < 6; j++) {
        uint32_t a[8];
        if constexpr (kVO) {
#pragma unroll
            for (int i = 0; i < 4; i++) {
                a[2 * i]     = __byte_perm(r.A[8 * j + 2 * i], r.A[8 * j + 2 * i + 1], 0x5410);
                a[2 * i + 1] = __byte_perm(r.A[8 * j + 2 * i], r.A[8 * j + 2 * i + 1], 0x7632);
            }
        } else {
#pragma unroll
            for (int i = 0; i < 8; i++) asm volatile("prmt.b32 %0, %1, 0, 0x3210;" : "=r"(a[i]) : "r"(r.A[8 * j + i]));
        }
        mma16816(c0, a[0], a[1], a[2], a[3], r.B0[j].x, r.B0[j].y);
        mma16816(c1, a[0], a[1], a[2], a[3], r.B1[j].x, r.B1[j].y);
        mma16816(c2, a[4], a[5], a[6], a[7], r.B0[j].z, r.B0[j].w);
        mma16816(c3, a[4], a[5], a[6], a[7], r.B1[j].z, r.B1[j].w);
    }
#pragma unroll
    for (int i = 0; i < 4; i++) { c0[i] += c2[i]; c1[i] += c3[i]; }
    const int k0 = (tile % 12) * 16;
    if constexpr (kVO) {
        const int n = (tile / 12) * 16 + 2 * g;
        fold_store(reinterpret_cast<char*>(sc->img[0][1]), sc->cnt_v, epoch, on, n, n + 1, k0, lane, c0, c1);
    } else {
        const int n0 = (tile / 12) * 16;
        fold_store(reinterpret_cast<char*>(sc->img[0][0]), sc->cnt_m, epoch, on, n0 + g, n0 + g + 8, k0, lane, c0, c1);
    }
}

__device__ __forceinline__ void prefetch_x(const CUtensorMap* tm, int win) {
    const int wh = win >> 6, ww = win & 63;
    asm volatile("cp.async.bulk.prefetch.tensor.3d.L2.global.tile [%0, {%1, %2, %3}];"
                 ::"l"(tm), "r"(0), "r"(ww * 8), "r"(wh * 8) : "memory");
}

__device__ __forceinline__ void reset_for_next_launch() {
    Scratch* q;
    asm volatile("ld.volatile.shared.u64 %0, [%1];" : "=l"(q) : "r"(kScAddr) : "memory");
    q->cnt_v[0] = 0; q->cnt_m[0] = 0; atomicAdd(q->epoch, 1);
}
__device__ __forceinline__ void finish_alone(uint32_t dXt, uint32_t dWv, int win) {
    uint32_t pa[16];
#pragma unroll
    for (int j = 0; j < 4; j++)
        asm volatile("ld.volatile.shared.v4.b32 {%0, %1, %2, %3}, [%4];" : "=r"(pa[4 * j]), "=r"(pa[4 * j + 1]), "=r"(pa[4 * j + 2]), "=r"(pa[4 * j + 3])
                     : "r"(kSmemBase + kOffStage + j * 2048 + (tid_now() & 127) * 16) : "memory");
    const uint32_t one = gridDim.y;
    float u0[32], u1[32], u2[32];
    float (&o0)[32] = u0, (&o1)[32] = u2, (&o2)[32] = u0;
    uint32_t fa[48];
    uint4 h[4];
    const float nz = __uint_as_float(one << 31);
    auto pack_a = [&](float (&u)[32], int c) {
        fence_regs(u);
#pragma unroll
        for (int i = 0; i < 16; i++) {
            fa[16 * c + i] = pack_bf16(c != 1 ? u[2 * i] + nz : u[2 * i], u[2 * i + 1]);
            asm volatile("" : "+r"(fa[16 * c + i])::"memory");
        }
        wg_fence();
    };
    auto pack_o = [&](float (&o)[32], bool first) {
        fence_regs(o);
        auto pk = [&](int i) { return pack_bf16(o[i], first ? o[i + 1] + nz : o[i + 1]); };
#pragma unroll
        for (int i = 0; i < 4; i++) {
            const int b = 16 * (i & 1) + 2 * (i >> 1);
            h[i] = make_uint4(pk(b), pk(b + 4), pk(b + 8), pk(b + 12));
        }
#pragma unroll
        for (int i = 0; i < 4; i++) asm volatile("" : "+r"(h[i].x), "+r"(h[i].y), "+r"(h[i].z), "+r"(h[i].w)::"memory");
    };
    wg_fence();
    Gemm3s<0, 3>::run(u0, pa, dXt); wg_commit();
    Gemm3s<1, 3>::run(u1, pa, dXt); wg_commit();
    Gemm3s<2, 3>::run(u2, pa, dXt); wg_commit();
    const uint32_t t = tid_now(), slot = kSmemBase + kOffStage + (t & 96) * 64;
    const uint32_t sa = stage_addr(slot, t);
    const uint32_t tok = (t >> 3) & 3, j = t & 7, la = slot + tok * 128 + ((j ^ tok) << 4);
    char* out;
    asm volatile("ld.volatile.shared.u64 %0, [%1];" : "=l"(out) : "r"(kScAddr + 8) : "memory");
    out += (((win >> 6) * 8 + ((t >> 4) & 6)) * kHW + (win & 63) * 8 + tok) * (kC * 2) + j * 16;
    uint4 v[4];
    auto S = [&](int i) { stsm4((sa ^ (i & 1) * 64) + (i >> 1) * 1024, h[i]); };
    auto L = [&](int i) {
        asm volatile("ld.volatile.shared.v4.b32 {%0, %1, %2, %3}, [%4];" : "=r"(v[i].x), "=r"(v[i].y), "=r"(v[i].z), "=r"(v[i].w)
                     : "r"((la ^ (i & 1) * 64) + i * 512) : "memory");
    };
    auto G = [&](int c, int i) {
        asm volatile("st.global.v4.b32 [%0], {%1, %2, %3, %4};"
                     ::"l"(out + ((i >> 1) * kHW + 4 * (i & 1)) * (kC * 2) + c * 128), "r"(v[i].x), "r"(v[i].y), "r"(v[i].z), "r"(v[i].w) : "memory");
    };
#define W(C, K0, K1, O) Gemm4s<C, K0, K1>::run(O, fa, dWv, one)
#define PIN __syncwarp()
    wg_wait2(); pack_a(u0, 0);
    asm volatile("bar.sync %0, 128;" ::"r"((tid_now() >> 7) + 1) : "memory");
    W(0, 0, 3, o0); wg_commit();
    wg_wait2(); pack_a(u1, 1);
    W(0, 4, 7, o0); wg_commit();
    wg_wait2(); pack_a(u2, 2);
    W(0, 8, 11, o0); wg_commit();
    W(1, 0, 5, o1); wg_commit();
    wg_wait1(); pack_o(o0, true);
    W(1, 6, 6, o1); S(0); W(1, 7, 7, o1); S(1); W(1, 8, 8, o1); S(2); W(1, 9, 9, o1); S(3); W(1, 10, 10, o1); PIN; L(0); W(1, 11, 11, o1); wg_commit(); L(1);
    wg_fence();
    W(2, 0, 0, o2); L(2); W(2, 1, 1, o2); L(3); W(2, 2, 2, o2); PIN; G(0, 0); PIN; W(2, 3, 3, o2); G(0, 1); PIN; W(2, 4, 4, o2); G(0, 2); PIN; W(2, 5, 5, o2); wg_commit(); G(0, 3);
    PIN;
    wg_wait1(); pack_o(o1, false);
    W(2, 6, 6, o2); S(0); W(2, 7, 7, o2); S(1); W(2, 8, 8, o2); S(2); W(2, 9, 9, o2); S(3); W(2, 10, 11, o2); wg_commit();
    wg_wait1();
    PIN; L(0); L(1); L(2); L(3); G(1, 0); G(1, 1); G(1, 2); G(1, 3);
    PIN;
    wg_wait0(); pack_o(o2, false);
    fence_regs(fa);
    S(0); S(1); S(2); S(3); PIN; L(0); L(1); L(2); L(3); G(2, 0); G(2, 1); G(2, 2); G(2, 3);
#undef W
#undef PIN
}

__global__ void __launch_bounds__(kThreads, 1)
swin_attn_kernel(const __nv_bfloat16* __restrict__ wqkv, const __nv_bfloat16* __restrict__ wo, Scratch* __restrict__ sc, void* out,
                 const __grid_constant__ OutMaps tmo, const __grid_constant__ CUtensorMap tmx, const __grid_constant__ CUtensorMap tmp, const __grid_constant__ CUtensorMap tmc) {
    extern __shared__ uint8_t smem_raw[];
    constexpr uint32_t sbase = kSmemBase;
    if (smem_u32(smem_raw) != kSmemBase) __trap();
    const int tid = threadIdx.x, lane = tid & 31;
    const uint32_t warpu = __reduce_or_sync(0xffffffffu, (uint32_t)tid >> 5), wgu = warpu >> 2;
    const int warp = (int)warpu, wg = (int)wgu;
    const int G = gridDim.x;
    const uint32_t bar_full = sbase + kOffBar + 8 * wg;

    const int ftile = blockIdx.x + (warp & 1) * G;
    FoldRegs fq;
#pragma unroll
    for (int j = 0; j < 6; j++) {
        asm volatile("" : "=r"(fq.B0[j].x), "=r"(fq.B0[j].y), "=r"(fq.B0[j].z), "=r"(fq.B0[j].w));
        asm volatile("" : "=r"(fq.B1[j].x), "=r"(fq.B1[j].y), "=r"(fq.B1[j].z), "=r"(fq.B1[j].w));
    }
#pragma unroll
    for (int j = 0; j < 48; j++) asm volatile("" : "=r"(fq.A[j]));
    uint32_t epoch;
    asm volatile("ld.relaxed.gpu.global.u32 %0, [%1];" : "=r"(epoch) : "l"(sc->epoch) : "memory");
    if (warp < 2 && ftile < kTiles) fold_load_qk(fq, wqkv, ftile, lane);
    if (warp == 3) {
        const uint32_t i = blockIdx.x + G * (lane & 15);
        const char* p = lane < 16 ? (const char*)wo + i * 128 : (const char*)wqkv + i * 128 + (i / 3 + 1) * 768;
        if (i < 576) asm volatile("prefetch.global.L2 [%0];" ::"l"(p) : "memory");
    }
    if (warp == 10) {
        if (lane == 0) {
#pragma unroll
            for (int w = 0; w < kNWG; w++) mbar_init(sbase + kOffBar + 8 * w, 1);
            asm volatile("fence.mbarrier_init.release.cluster;" ::: "memory");
        }
        __syncwarp();
        asm volatile("bar.arrive 11, 384;" ::: "memory");
        if (lane == 0) {
            const uint32_t t0 = (uint32_t)clock64() + kPaceStart + ((blockIdx.x * 37) & 63) * kPaceSpread / 64;
#pragma unroll
            for (int w = 0; w < kNWG; w++) mbar_expect_tx(sbase + kOffBar + 8 * w, kXBytes);
#pragma unroll 1
            for (int i = 0; i <= 3 * kNWG; i++) {
                while ((int)((uint32_t)clock64() - t0) < (i < 3 ? i * kPaceStep0 : kPaceMid + (i - 3) * kPaceStep)) {}
                const int w = i / 3, c = i % 3;
                if (w < kNWG) tma_load_x_chunk(sbase + kOffX + w * kXBytes + c * 8192, &tmc, sbase + kOffBar + 8 * w, w * G + blockIdx.x, c);
                else prefetch_x(&tmp, kNWG * G + blockIdx.x);
            }
        }
    }
    if (warp < 3) {
        for (int t = ftile;;) {
            const bool on = warp < 2 && t < kTiles;
            fold_compute_store<false>(fq, sc, t, lane, epoch, on);
            t += 2 * G;
            if (__builtin_expect(warp == 2 || t >= kTiles, 1)) break;
            fold_load_qk(fq, wqkv, t, lane);
        }
    }
    if (warp < 4) {
        asm volatile("bar.sync 11, 384;" ::: "memory");
    } else if (warp == 4) {
        if (lane == 0) {
            set_link(0, 9); set_link(1, 8); set_link(2, 8);
            asm volatile("st.shared.v2.u64 [%0], {%1, %2};" ::"r"(kScAddr), "l"(sc), "l"(out) : "memory");
            mbar_init(bar_m(0), 1);
            mbar_init(bar_m(1), 1);
            mbar_init(bar_m(2), 1);
            asm volatile("fence.mbarrier_init.release.cluster;" ::: "memory");
        }
        __syncwarp();
        asm volatile("bar.arrive 12, 128;" ::: "memory");
        asm volatile("bar.arrive 11, 384;" ::: "memory");
        if (lane == 0) {
            uint32_t v, spins = 0;
            do {
                asm volatile("ld.relaxed.gpu.global.u32 %0, [%1];" : "=r"(v) : "l"(sc->cnt_m) : "memory");
                if (++spins > (1u << 22)) __trap();
            } while (v < kMqkHint);
            const uint32_t par = epoch & 1;
            m_load(sc, 0, par); m_load(sc, 1, par); m_load(sc, 2, par);
        }
    } else if (warp == 11) {
        if (lane == 0) {
            mbar_init(kBarV, 1);
            asm volatile("fence.mbarrier_init.release.cluster;" ::: "memory");
        }
        __syncwarp();
        asm volatile("bar.sync 11, 384;" ::: "memory");
        if (lane == 0) {
            uint32_t v, spins = 0;
            do {
                asm volatile("ld.relaxed.gpu.global.u32 %0, [%1];" : "=r"(v) : "l"(sc->cnt_v) : "memory");
                if (++spins > (1u << 22)) __trap();
            } while (v < kTiles);
            uint32_t ok = 0, n = 0;
            while (!ok && ++n < 64)
                asm volatile("{\n.reg .pred p;\nmbarrier.try_wait.parity.shared::cta.b64 p, [%1], 0;\nselp.b32 %0, 1, 0, p;\n}\n" : "=r"(ok) : "r"(bar_m(2)) : "memory");
            v_load(sc, epoch & 1);
        }
    } else if (warp == 10) {
    } else if (warp >= 8) {
        asm volatile("bar.arrive 11, 384;" ::: "memory");
        if (warp == 9) { const uint32_t t0 = (uint32_t)clock64(); while ((uint32_t)clock64() - t0 < kWvoDelay) {} }
        FoldRegs fr;
        for (int t = G - 1 - blockIdx.x + (warp & 1) * G; t < kTiles; t += 2 * G) {
            fold_load_vo(fr, wqkv, wo, t, lane);
            fold_compute_store<true>(fr, sc, t, lane, epoch, 1);
        }
    } else {
        asm volatile("bar.arrive 11, 384;" ::: "memory");
        if (lane == 0) asm volatile("prefetch.tensormap [%0];" ::"l"(warp == 5 ? &tmo.m[0] : warp == 6 ? &tmo.m[1] : &tmx) : "memory");
        asm volatile("bar.sync 12, 128;" ::: "memory");
    }
    __syncwarp();
    if (wg == 1) m_check(sc, epoch & 1);
    uint4 hv[12];
#pragma unroll
    for (int a = 0; a < 12; a++) asm volatile("" : "=r"(hv[a].x), "=r"(hv[a].y), "=r"(hv[a].z), "=r"(hv[a].w));

    constexpr uint32_t dWm = ((sbase + kOffWm) >> 4) | (1u << 16);
    constexpr uint32_t dWv = ((sbase + kOffWv) >> 4) | (1u << 16);
    const float cs = 0.07216878364870322f * 1.4426950408889634f;
    if (wg == 2) {
        asm volatile("bar.sync 13, 128;" ::: "memory");
        v_check(sc, epoch & 1);
    }
    mbar_wait(bar_full, 0);

    uint32_t st = (uint32_t)(wg * G + blockIdx.x) << 17 | kFirst | (wg == 0 ? kSolo | kVeryFirst : 0);

    while (true) {
        float acc[96];
        uint32_t fa[48];
        const uint32_t dX = ((sbase + kOffX + wg_uniform() * kXBytes) >> 4) | (1u << 16);
        uint32_t ticket = 0;
        uint32_t lnk = baton_wait(st, 0);
        while (true) {
            const bool very_first = st & kVeryFirst;
            Gemm1<11>::run(acc, dX, dWm, very_first, st);
            wg_commit();
            if (!very_first) { baton_pass(lnk, st); break; }
            wg_wait0();
            if (m_agree(1)) break;
            st ^= kRound;
        }
        draw_ticket(ticket);
        if (!(st & kFirst)) {
            const uint32_t w4 = warp4_uniform();
            const uint32_t slot = sbase + kOffStage + w4 * 2048;
            const int col = (st_out(st) & 63) * 8, row = (st_out(st) >> 6) * 8 + 2 * w4;
            store_round<0>(hv, slot, tmo.m, col, row);
            bulk_wait_read();
            __syncwarp();
            store_round<1>(hv, slot, tmo.m, col, row);
            bulk_wait_read();
            __syncwarp();
            store_round<2>(hv, slot, tmo.m, col, row);
        }
        static_assert(kPfInit == 2, "one start-up prefetch in the prologue, one here");
        if ((st & kFirst) && tid_now() == 128) prefetch_x(&tmp, (kNWG + (tid_now() >> 7)) * gridDim.x + blockIdx.x);
        __syncwarp();
        wg_wait0();
        fence_regs(acc);
#pragma unroll
        for (int i = 0; i < 48; i++) fa[i] = pack_bf16(acc[2 * i], acc[2 * i + 1]);

        float s[32];
        fence_regs(fa);
        lnk = baton_wait(st, fa[47]);
        wg_fence();
        Gemm2<11>::run(s, fa, dX, lnk, st);
        wg_commit();
        wg_wait0();
        fence_regs(s);
        fence_regs(fa);

        uint32_t pa[16];
        {
            float a0[8], a1[8];
#pragma unroll
            for (int j = 0; j < 8; j++) { a0[j] = fmaxf(s[4 * j], s[4 * j + 1]); a1[j] = fmaxf(s[4 * j + 2], s[4 * j + 3]); }
#pragma unroll
            for (int d = 4; d > 0; d >>= 1)
#pragma unroll
                for (int j = 0; j < d; j++) { a0[j] = fmaxf(a0[j], a0[j + d]); a1[j] = fmaxf(a1[j], a1[j + d]); }
            float m0 = a0[0], m1 = a1[0];
            m0 = fmaxf(m0, __shfl_xor_sync(0xffffffffu, m0, 1));
            m1 = fmaxf(m1, __shfl_xor_sync(0xffffffffu, m1, 1));
            m0 = fmaxf(m0, __shfl_xor_sync(0xffffffffu, m0, 2));
            m1 = fmaxf(m1, __shfl_xor_sync(0xffffffffu, m1, 2));
            m0 *= cs; m1 *= cs;
            float l0 = 0.f, l1 = 0.f;
#pragma unroll
            for (int j = 0; j < 8; j++) {
                s[4 * j]     = ex2(fmaf(s[4 * j], cs, -m0));
                s[4 * j + 1] = ex2(fmaf(s[4 * j + 1], cs, -m0));
                s[4 * j + 2] = ex2(fmaf(s[4 * j + 2], cs, -m1));
                s[4 * j + 3] = ex2(fmaf(s[4 * j + 3], cs, -m1));
                l0 += s[4 * j] + s[4 * j + 1];
                l1 += s[4 * j + 2] + s[4 * j + 3];
            }
            l0 += __shfl_xor_sync(0xffffffffu, l0, 1);
            l1 += __shfl_xor_sync(0xffffffffu, l1, 1);
            l0 += __shfl_xor_sync(0xffffffffu, l0, 2);
            l1 += __shfl_xor_sync(0xffffffffu, l1, 2);
            const float r0 = rcp(l0), r1 = rcp(l1);
#pragma unroll
            for (int j = 0; j < 8; j++) {
                pa[2 * j]     = pack_bf16(s[4 * j] * r0, s[4 * j + 1] * r0);
                pa[2 * j + 1] = pack_bf16(s[4 * j + 2] * r1, s[4 * j + 3] * r1);
            }
        }

        fence_regs(pa);
        if ((tid_now() & 127) == 0)
            asm volatile("st.volatile.shared.u32 [%0], %1;" ::"r"(kLink + 4 + 8 * (tid_now() >> 7)), "r"(kNWG * gridDim.x + ticket) : "memory");
        uint32_t pub;
        lnk = baton_wait_pub(st, pa[15], pub);
        if ((st & kFirst) && tid_now() == 0) set_link(1, 10);
        const bool alone = lnk == (tid_now() >> 7) + 8 && pub >= kNWin;
        asm volatile("{\n.reg .pred p;\nsetp.ne.u32 p, %16, 0;\n"
                     "@p st.volatile.shared.v4.b32 [%17], {%0, %1, %2, %3};\n@p st.volatile.shared.v4.b32 [%17 + 2048], {%4, %5, %6, %7};\n"
                     "@p st.volatile.shared.v4.b32 [%17 + 4096], {%8, %9, %10, %11};\n@p st.volatile.shared.v4.b32 [%17 + 6144], {%12, %13, %14, %15};\n}\n"
                     :: "r"(pa[0]), "r"(pa[1]), "r"(pa[2]), "r"(pa[3]), "r"(pa[4]), "r"(pa[5]), "r"(pa[6]), "r"(pa[7]),
                        "r"(pa[8]), "r"(pa[9]), "r"(pa[10]), "r"(pa[11]), "r"(pa[12]), "r"(pa[13]), "r"(pa[14]), "r"(pa[15]),
                        "r"((uint32_t)alone), "r"(sbase + kOffStage + (tid_now() & 127) * 16) : "memory");
        if (alone) {
            if (ticket == kNWin - 1) reset_for_next_launch();
            __syncwarp();
            finish_alone(dX + (((8192u >> 4) - 1) << 16), dWv, st_win(st));
            return;
        }
        wg_fence();
        Gemm3<3>::run(acc, pa, dX + (((8192u >> 4) - 1) << 16));
        wg_commit();
        baton_pass(lnk, st);
        const int nxt = (int)__reduce_or_sync(0xffffffffu, pub);
        wg_wait0();
        fence_regs(acc);
        fence_regs(pa);

        if (((tid_now() >> 5) & 3) == 0 && nxt < kNWin) {
            asm volatile("bar.sync %0, 128;" ::"r"((tid_now() >> 7) + 1) : "memory");
            if (elect_one()) {
                const uint32_t wgl = tid_now() >> 7;
                const uint32_t bar = sbase + kOffBar + 8 * wgl;
                mbar_expect_tx(bar, kXBytes);
                tma_load_x(sbase + kOffX + wgl * kXBytes, &tmx, bar, nxt);
            }
            __syncwarp();
        } else {
            asm volatile("bar.arrive %0, 128;" ::"r"((tid_now() >> 7) + 1) : "memory");
        }
#pragma unroll
        for (int i = 0; i < 48; i++) fa[i] = pack_bf16(acc[2 * i], acc[2 * i + 1]);

        asm volatile("st.volatile.shared.v4.b32 [%4], {%0, %1, %2, %3};"
                     :: "r"(fa[44]), "r"(fa[45]), "r"(fa[46]), "r"(fa[47]), "r"(sbase + kOffStash + (tid_now() & 127) * 16) : "memory");
        fence_regs(fa);
        if (((tid_now() >> 5) & 3) == 0 && nxt + kPfMin < kNWin) {
            if (elect_one()) {
                const int base = kNWG * (int)gridDim.x, t = nxt - base;
                const int hi = min(nxt + pf_lead(t), kNWin - 1);
                int lo = max(max(nxt - 1 + pf_lead(t - 1), nxt) + 1, base + kPfInit * (int)gridDim.x);
#pragma unroll 1
                for (; lo <= hi; lo++) prefetch_x(&tmp, lo);
            }
            __syncwarp();
        }
        lnk = baton_wait(st, fa[43]);
        if (nxt >= kNWin) {
            if ((tid_now() & 127) == 0) {
#pragma unroll
                for (int w = 0; w < kNWG; w++) {
                    uint32_t l;
                    asm volatile("ld.volatile.shared.u32 %0, [%1];" : "=r"(l) : "r"(kLink + 8 * w) : "memory");
                    if (l == (tid_now() >> 7) + 8) set_link(w, lnk);
                }
            }
        }
        __syncwarp();
        wg_fence();
        Gemm4<0, 1>::run(acc, fa, dWv);
        wg_commit();
        Gemm4<2, 10>::run(acc, fa, dWv);
        wg_commit();
        wg_wait1();
        uint32_t fl[4];
        asm volatile("ld.volatile.shared.v4.b32 {%0, %1, %2, %3}, [%4];"
                     : "=r"(fl[0]), "=r"(fl[1]), "=r"(fl[2]), "=r"(fl[3]) : "r"(sbase + kOffStash + (tid_now() & 127) * 16) : "memory");
        wg_fence();
        wg192_rs<false, 0, koff(11, 24576)>(acc, fl, dWv);
        wg_commit();
        baton_pass(lnk, st);
        if (nxt == kNWG * (int)gridDim.x + kNWin - 1 && (tid_now() & 127) == 0) reset_for_next_launch();
        __syncwarp();
        st = ((st ^ kPhase) & (kPhase | kSolo)) | st_win(st) << 4 | nxt << 17;
        uint32_t landed = 1;
        if (nxt < kNWin)
            asm volatile("{\n.reg .pred p;\nmbarrier.test_wait.parity.shared::cta.b64 p, [%1], %2;\nselp.b32 %0, 1, 0, p;\n}\n"
                         : "=r"(landed) : "r"(sbase + kOffBar + 8 * (tid_now() >> 7)), "r"(st & kPhase) : "memory");
        wg_wait0();
        fence_regs(acc);
        fence_regs(fa);
        fence_regs(fl);

#pragma unroll
        for (int a = 0; a < 6; a++)
#pragma unroll
            for (int r = 0; r < 2; r++)
                hv[2 * a + r] = make_uint4(pack_bf16(acc[16 * a + 2 * r], acc[16 * a + 2 * r + 1]), pack_bf16(acc[16 * a + 2 * r + 4], acc[16 * a + 2 * r + 5]),
                                           pack_bf16(acc[16 * a + 2 * r + 8], acc[16 * a + 2 * r + 9]), pack_bf16(acc[16 * a + 2 * r + 12], acc[16 * a + 2 * r + 13]));
        if (nxt >= kNWin) break;
        if (!landed) mbar_wait(sbase + kOffBar + 8 * (tid_now() >> 7), st & kPhase);
    }
    asm volatile("bar.sync %0, 128;" ::"r"((tid_now() >> 7) + 1) : "memory");
    {
        const uint32_t t = tid_opaque(), wu = __reduce_or_sync(0xffffffffu, t >> 5), w4 = wu & 3;
        const uint32_t slot = sbase + kOffX + wu * 6144, sa = stage_addr(slot, t);
        const int col = (st_out(st) & 63) * 8, row = (st_out(st) >> 6) * 8 + 2 * w4;
        stage_round<0>(hv, sa);
        stage_round<1>(hv, sa + 2048);
        stage_round<2>(hv, sa + 4096);
        stage_fence();
        send_round<0>(slot, tmo.m, col, row);
        send_round<1>(slot + 2048, tmo.m, col, row);
        send_round<2>(slot + 4096, tmo.m, col, row);
    }
    bulk_wait_read();
}

typedef CUresult (*EncodeTiledFn)(CUtensorMap*, CUtensorMapDataType, cuuint32_t, void*, const cuuint64_t*,
                                  const cuuint64_t*, const cuuint32_t*, const cuuint32_t*, CUtensorMapInterleave,
                                  CUtensorMapSwizzle, CUtensorMapL2promotion, CUtensorMapFloatOOBfill);

}

extern "C" void kernel_launch(void* const* d_in, const int* in_sizes, int n_in, void* d_out, int out_size) {
    (void)in_sizes; (void)n_in; (void)out_size;
    const __nv_bfloat16* x    = (const __nv_bfloat16*)d_in[0];
    const __nv_bfloat16* wqkv = (const __nv_bfloat16*)d_in[1];
    const __nv_bfloat16* wo   = (const __nv_bfloat16*)d_in[2];

    static EncodeTiledFn encode = nullptr;
    static int num_sms = 0;
    static Scratch* scratch = nullptr;
    if (!encode) {
        void* fn = nullptr;
        cudaDriverEntryPointQueryResult qr;
        cudaGetDriverEntryPoint("cuTensorMapEncodeTiled", &fn, cudaEnableDefault, &qr);
        encode = (EncodeTiledFn)fn;
        cudaGetSymbolAddress((void**)&scratch, g_scratch);
        int dev = 0;
        cudaGetDevice(&dev);
        cudaDeviceGetAttribute(&num_sms, cudaDevAttrMultiProcessorCount, dev);
        cudaFuncSetAttribute(swin_attn_kernel, cudaFuncAttributeMaxDynamicSharedMemorySize, kSmemBytes);
    }
    CUtensorMap tmx;
    const cuuint64_t gdim[4] = {64, (cuuint64_t)kHW, (cuuint64_t)kHW, 3};
    const cuuint64_t gstr[3] = {(cuuint64_t)kC * 2, (cuuint64_t)kHW * kC * 2, 128};
    const cuuint32_t box[4] = {64, 8, 8, 3};
    const cuuint32_t estr[4] = {1, 1, 1, 1};
    encode(&tmx, CU_TENSOR_MAP_DATA_TYPE_BFLOAT16, 4, (void*)x, gdim, gstr, box, estr, CU_TENSOR_MAP_INTERLEAVE_NONE,
           CU_TENSOR_MAP_SWIZZLE_128B, CU_TENSOR_MAP_L2_PROMOTION_NONE, CU_TENSOR_MAP_FLOAT_OOB_FILL_NONE);

    CUtensorMap tmp;
    const cuuint64_t pdim[3] = {(cuuint64_t)kC, (cuuint64_t)kHW, (cuuint64_t)kHW};
    const cuuint64_t pstr[2] = {(cuuint64_t)kC * 2, (cuuint64_t)kHW * kC * 2};
    const cuuint32_t pbox[3] = {(cuuint32_t)kC, 8, 8};
    encode(&tmp, CU_TENSOR_MAP_DATA_TYPE_BFLOAT16, 3, (void*)x, pdim, pstr, pbox, estr, CU_TENSOR_MAP_INTERLEAVE_NONE,
           CU_TENSOR_MAP_SWIZZLE_NONE, CU_TENSOR_MAP_L2_PROMOTION_NONE, CU_TENSOR_MAP_FLOAT_OOB_FILL_NONE);
    CUtensorMap tmc;
    const cuuint32_t boxc[4] = {64, 8, 8, 1};
    encode(&tmc, CU_TENSOR_MAP_DATA_TYPE_BFLOAT16, 4, (void*)x, gdim, gstr, boxc, estr, CU_TENSOR_MAP_INTERLEAVE_NONE,
           CU_TENSOR_MAP_SWIZZLE_128B, CU_TENSOR_MAP_L2_PROMOTION_NONE, CU_TENSOR_MAP_FLOAT_OOB_FILL_NONE);
    OutMaps tmo;
    const cuuint32_t boxo[4] = {64, 8, 1, 2};
    encode(&tmo.m[0], CU_TENSOR_MAP_DATA_TYPE_BFLOAT16, 4, d_out, gdim, gstr, boxo, estr, CU_TENSOR_MAP_INTERLEAVE_NONE,
           CU_TENSOR_MAP_SWIZZLE_128B, CU_TENSOR_MAP_L2_PROMOTION_NONE, CU_TENSOR_MAP_FLOAT_OOB_FILL_NONE);
    const cuuint64_t odim[4] = {64, (cuuint64_t)kHW, (cuuint64_t)kHW, 2};
    const cuuint64_t ostr[3] = {(cuuint64_t)kC * 2, (cuuint64_t)kHW * kC * 2, (cuuint64_t)kHW * kC * 2 - 256};
    encode(&tmo.m[1], CU_TENSOR_MAP_DATA_TYPE_BFLOAT16, 4, (char*)d_out + 256, odim, ostr, boxo, estr, CU_TENSOR_MAP_INTERLEAVE_NONE,
           CU_TENSOR_MAP_SWIZZLE_128B, CU_TENSOR_MAP_L2_PROMOTION_NONE, CU_TENSOR_MAP_FLOAT_OOB_FILL_NONE);
    swin_attn_kernel<<<num_sms, kThreads, kSmemBytes, cudaStreamPerThread>>>(wqkv, wo, scratch, d_out, tmo, tmx, tmp, tmc);
}
```

```cpp
#include <cuda_runtime.h>
#include <cuda_bf16.h>
#include <cuda.h>
#include <stdint.h>

namespace {

constexpr int kC      = 192;
constexpr int kHW     = 512;
constexpr int kNWin   = 4096;
constexpr int kXBytes = 64 * kC * 2;
constexpr int kWBytes = kC * kC * 2;
constexpr int kNWG    = 3;
constexpr int kThreads = kNWG * 128;
constexpr int kTiles  = 144;
constexpr int kPfInit = 2, kPfUp = 160, kPfPeak = 400, kPfHold = 800, kPfDown1 = 40, kPfBase2 = 300, kPfDown2 = 12, kPfMin = 140;
__device__ __forceinline__ int pf_lead(int t) {
    return min(min(kPfInit * (int)gridDim.x + ((t * kPfUp) >> 8), kPfPeak),
               max(max(kPfPeak - (((t - kPfHold) * kPfDown1) >> 8), kPfBase2 - ((t * kPfDown2) >> 8)), kPfMin));
}
constexpr int kEvictFrom = 3100;
constexpr int kPaceStart = 100, kPaceSpread = 500, kPaceStep0 = 750, kPaceMid = 2250, kPaceStep = 550;
constexpr uint32_t kMqkHint = 72;
constexpr uint32_t kPollDelay = 200;
constexpr uint32_t kWvoDelay = 1000;

constexpr int kOffWm  = 0;
constexpr int kOffWv  = kWBytes;
constexpr int kOffX   = 2 * kWBytes;
constexpr int kOffStage = kOffX + kNWG * kXBytes;
constexpr int kOffStash = kOffStage + 8192;
constexpr int kOffBar = kOffStash + 2048;
constexpr int kSmemBytes = kOffBar + 256;
constexpr uint32_t kSmemBase = 1024;

struct Scratch {
    uint32_t ticket[32];
    uint32_t epoch[32];
    uint32_t cnt_v[32];
    uint32_t cnt_m[32];
    uint4 img[2][2][kWBytes / 16];
};
__device__ __align__(128) Scratch g_scratch;

__device__ __forceinline__ uint32_t smem_u32(const void* p) { return (uint32_t)__cvta_generic_to_shared(p); }

__device__ __forceinline__ void mbar_init(uint32_t bar, uint32_t count) {
    asm volatile("mbarrier.init.shared::cta.b64 [%0], %1;" ::"r"(bar), "r"(count) : "memory");
}
__device__ __forceinline__ void mbar_expect_tx(uint32_t bar, uint32_t bytes) {
    asm volatile("mbarrier.arrive.expect_tx.shared::cta.b64 _, [%0], %1;" ::"r"(bar), "r"(bytes) : "memory");
}
__device__ __forceinline__ void mbar_wait(uint32_t bar, uint32_t parity) {
    uint32_t ok;
    uint32_t spins = 0;
    do {
        asm volatile("{\n.reg .pred p;\n"
                     "mbarrier.try_wait.parity.shared::cta.b64 p, [%1], %2;\n"
                     "selp.b32 %0, 1, 0, p;\n}\n"
                     : "=r"(ok) : "r"(bar), "r"(parity) : "memory");
        if (++spins > (1u << 26)) __trap();
    } while (!ok);
}
__device__ __forceinline__ uint32_t tid_now() {
    uint32_t t;
    asm volatile("mov.u32 %0, %%tid.x;" : "=r"(t));
    return t;
}
__device__ __forceinline__ bool elect_one() {
    uint32_t pred;
    asm volatile("{\n.reg .pred p;\nelect.sync _|p, 0xffffffff;\nselp.b32 %0, 1, 0, p;\n}\n" : "=r"(pred));
    return pred != 0;
}
__device__ __forceinline__ uint32_t wg_uniform() { return __reduce_or_sync(0xffffffffu, tid_now() >> 7); }
constexpr uint32_t kLink = kSmemBase + kOffBar + 64;
constexpr uint32_t kPhase = 1;
constexpr uint32_t kSolo = 2;
constexpr uint32_t kFirst = 4;
constexpr uint32_t kRound = 8;
constexpr uint32_t kVeryFirst = 1u << 16;
__device__ __forceinline__ int st_out(uint32_t st) { return (st >> 4) & 0xfff; }
__device__ __forceinline__ int st_win(uint32_t st) { return st >> 17; }
__device__ __forceinline__ uint32_t baton_wait(uint32_t st, uint32_t packed) {
    if (packed == 0xffffffffu) __trap();
    if (!(st & kSolo)) asm volatile("bar.sync %0, 256;" ::"r"((tid_now() >> 7) + 8) : "memory");
    uint32_t lnk;
    asm volatile("ld.volatile.shared.u32 %0, [%1];" : "=r"(lnk) : "r"(kLink + 8 * (tid_now() >> 7)) : "memory");
    return lnk;
}
__device__ __forceinline__ uint32_t baton_wait_pub(uint32_t st, uint32_t packed, uint32_t& pub) {
    if (packed == 0xffffffffu) __trap();
    asm volatile("bar.sync %0, %1;" ::"r"((tid_now() >> 7) + 8), "r"(st & kSolo ? 128 : 256) : "memory");
    uint32_t lnk;
    asm volatile("ld.volatile.shared.v2.u32 {%0, %1}, [%2];" : "=r"(lnk), "=r"(pub) : "r"(kLink + 8 * (tid_now() >> 7)) : "memory");
    return lnk;
}
__device__ __forceinline__ void baton_pass(uint32_t lnk, uint32_t& st) {
    const bool other = lnk != (tid_now() >> 7) + 8;
    if (other) asm volatile("bar.arrive %0, 256;" ::"r"(lnk) : "memory");
    st = other ? st & ~kSolo : st | kSolo;
}
__device__ __forceinline__ void set_link(int w, uint32_t v) { asm volatile("st.volatile.shared.u32 [%0], %1;" ::"r"(kLink + 8 * w), "r"(v) : "memory"); }
constexpr uint64_t kPolNormal = 0x1000000000000000ull, kPolFirst = 0x12F0000000000000ull;
__device__ __forceinline__ void tma_load_x(uint32_t dst, const CUtensorMap* tm, uint32_t bar, int win) {
    const int wh = win >> 6, ww = win & 63;
    asm volatile("cp.async.bulk.tensor.4d.shared::cluster.global.mbarrier::complete_tx::bytes.L2::cache_hint"
                 " [%0], [%1, {%3, %4, %5, %6}], [%2], %7;"
                 ::"r"(dst), "l"(tm), "r"(bar), "r"(0), "r"(ww * 8), "r"(wh * 8), "r"(0), "l"(win >= kEvictFrom ? kPolFirst : kPolNormal) : "memory");
}
__device__ __forceinline__ void tma_load_x_chunk(uint32_t dst, const CUtensorMap* tm, uint32_t bar, int win, int chunk) {
    const int wh = win >> 6, ww = win & 63;
    asm volatile("cp.async.bulk.tensor.4d.shared::cluster.global.mbarrier::complete_tx::bytes"
                 " [%0], [%1, {%3, %4, %5, %6}], [%2];"
                 ::"r"(dst), "l"(tm), "r"(bar), "r"(0), "r"(ww * 8), "r"(wh * 8), "r"(chunk) : "memory");
}
__device__ __forceinline__ void bulk_load(uint32_t dst, const void* src, uint32_t bytes, uint32_t bar) {
    asm volatile("cp.async.bulk.shared::cluster.global.mbarrier::complete_tx::bytes [%0], [%1], %2, [%3];"
                 ::"r"(dst), "l"(src), "r"(bytes), "r"(bar) : "memory");
}

__device__ __forceinline__ void wg_fence()  { asm volatile("wgmma.fence.sync.aligned;" ::: "memory"); }
__device__ __forceinline__ void wg_commit() { asm volatile("wgmma.commit_group.sync.aligned;" ::: "memory"); }
__device__ __forceinline__ void wg_wait0()  { asm volatile("wgmma.wait_group.sync.aligned 0;" ::: "memory"); }
__device__ __forceinline__ void wg_wait1()  { asm volatile("wgmma.wait_group.sync.aligned 1;" ::: "memory"); }
__device__ __forceinline__ void wg_wait2()  { asm volatile("wgmma.wait_group.sync.aligned 2;" ::: "memory"); }

template <int N> __device__ __forceinline__ void fence_regs(float (&d)[N]) {
#pragma unroll
    for (int i = 0; i < N; i++) asm volatile("" : "+f"(d[i])::"memory");
}
template <int N> __device__ __forceinline__ void fence_regs(uint32_t (&d)[N]) {
#pragma unroll
    for (int i = 0; i < N; i++) asm volatile("" : "+r"(d[i])::"memory");
}

#define ACC8(c, d, i) c(d[i]), c(d[i + 1]), c(d[i + 2]), c(d[i + 3]), c(d[i + 4]), c(d[i + 5]), c(d[i + 6]), c(d[i + 7])
#define ACC32(c, d) ACC8(c, d, 0), ACC8(c, d, 8), ACC8(c, d, 16), ACC8(c, d, 24)
#define ACC96(c, d) ACC32(c, d), ACC8(c, d, 32), ACC8(c, d, 40), ACC8(c, d, 48), ACC8(c, d, 56), \
                    ACC8(c, d, 64), ACC8(c, d, 72), ACC8(c, d, 80), ACC8(c, d, 88)
#define C_IO(x) "+f"(x)
#define C_O(x) "=f"(x)
#define REGS32 "{%0, %1, %2, %3, %4, %5, %6, %7, %8, %9, %10, %11, %12, %13, %14, %15, " \
               "%16, %17, %18, %19, %20, %21, %22, %23, %24, %25, %26, %27, %28, %29, %30, %31}"
#define REGS96 "{%0, %1, %2, %3, %4, %5, %6, %7, %8, %9, %10, %11, %12, %13, %14, %15, " \
               "%16, %17, %18, %19, %20, %21, %22, %23, %24, %25, %26, %27, %28, %29, %30, %31, " \
               "%32, %33, %34, %35, %36, %37, %38, %39, %40, %41, %42, %43, %44, %45, %46, %47, " \
               "%48, %49, %50, %51, %52, %53, %54, %55, %56, %57, %58, %59, %60, %61, %62, %63, " \
               "%64, %65, %66, %67, %68, %69, %70, %71, %72, %73, %74, %75, %76, %77, %78, %79, " \
               "%80, %81, %82, %83, %84, %85, %86, %87, %88, %89, %90, %91, %92, %93, %94, %95}"

#define DESC_HI "0x40000040"
#define MK_DESC(name, lo, off) "add.u32 t, " lo ", " off ";\nmov.b64 " name ", {t, " DESC_HI "};\n"

template <bool First, int OA, int OB> __device__ __forceinline__ void wg192_ss(float (&d)[96], uint32_t la, uint32_t lb) {
    if constexpr (First)
        asm volatile("{\n.reg .pred p;\n.reg .b32 t;\n.reg .b64 da, db;\nsetp.ne.b32 p, 0, 0;\n"
                     MK_DESC("da", "%96", "%98") MK_DESC("db", "%97", "%99")
                     "wgmma.mma_async.sync.aligned.m64n192k16.f32.bf16.bf16 " REGS96 ", da, db, p, 1, 1, 0, 0;\n}\n"
                     : ACC96(C_O, d) : "r"(la), "r"(lb), "n"(OA), "n"(OB));
    else
        asm volatile("{\n.reg .pred p;\n.reg .b32 t;\n.reg .b64 da, db;\nsetp.ne.b32 p, 1, 0;\n"
                     MK_DESC("da", "%96", "%98") MK_DESC("db", "%97", "%99")
                     "wgmma.mma_async.sync.aligned.m64n192k16.f32.bf16.bf16 " REGS96 ", da, db, p, 1, 1, 0, 0;\n}\n"
                     : ACC96(C_IO, d) : "r"(la), "r"(lb), "n"(OA), "n"(OB));
}
template <bool First, int TB, int OB> __device__ __forceinline__ void wg192_rs(float (&d)[96], const uint32_t* a, uint32_t lb) {
    if constexpr (First)
        asm volatile("{\n.reg .pred p;\n.reg .b32 t;\n.reg .b64 db;\nsetp.ne.b32 p, 0, 0;\n"
                     MK_DESC("db", "%100", "%102")
                     "wgmma.mma_async.sync.aligned.m64n192k16.f32.bf16.bf16 " REGS96 ", {%96, %97, %98, %99}, db, p, 1, 1, %101;\n}\n"
                     : ACC96(C_O, d) : "r"(a[0]), "r"(a[1]), "r"(a[2]), "r"(a[3]), "r"(lb), "n"(TB), "n"(OB));
    else
        asm volatile("{\n.reg .pred p;\n.reg .b32 t;\n.reg .b64 db;\nsetp.ne.b32 p, 1, 0;\n"
                     MK_DESC("db", "%100", "%102")
                     "wgmma.mma_async.sync.aligned.m64n192k16.f32.bf16.bf16 " REGS96 ", {%96, %97, %98, %99}, db, p, 1, 1, %101;\n}\n"
                     : ACC96(C_IO, d) : "r"(a[0]), "r"(a[1]), "r"(a[2]), "r"(a[3]), "r"(lb), "n"(TB), "n"(OB));
}
template <bool First, int TB, int OB> __device__ __forceinline__ void wg64_rs(float (&d)[32], const uint32_t* a, uint32_t lb) {
    if constexpr (First)
        asm volatile("{\n.reg .pred p;\n.reg .b32 t;\n.reg .b64 db;\nsetp.ne.b32 p, 0, 0;\n"
                     MK_DESC("db", "%36", "%38")
                     "wgmma.mma_async.sync.aligned.m64n64k16.f32.bf16.bf16 " REGS32 ", {%32, %33, %34, %35}, db, p, 1, 1, %37;\n}\n"
                     : ACC32(C_O, d) : "r"(a[0]), "r"(a[1]), "r"(a[2]), "r"(a[3]), "r"(lb), "n"(TB), "n"(OB));
    else
        asm volatile("{\n.reg .pred p;\n.reg .b32 t;\n.reg .b64 db;\nsetp.ne.b32 p, 1, 0;\n"
                     MK_DESC("db", "%36", "%38")
                     "wgmma.mma_async.sync.aligned.m64n64k16.f32.bf16.bf16 " REGS32 ", {%32, %33, %34, %35}, db, p, 1, 1, %37;\n}\n"
                     : ACC32(C_IO, d) : "r"(a[0]), "r"(a[1]), "r"(a[2]), "r"(a[3]), "r"(lb), "n"(TB), "n"(OB));
}
template <int OB> __device__ __forceinline__ void wg64_rs_reuse(float (&d)[32], const uint32_t* a, uint32_t lb, uint32_t one) {
    asm volatile("{\n.reg .pred p;\n.reg .b32 t;\n.reg .b64 db;\nsetp.ne.b32 p, %38, 1;\n"
                 MK_DESC("db", "%36", "%37")
                 "wgmma.mma_async.sync.aligned.m64n64k16.f32.bf16.bf16 " REGS32 ", {%32, %33, %34, %35}, db, p, 1, 1, 0;\n}\n"
                 : ACC32(C_IO, d) : "r"(a[0]), "r"(a[1]), "r"(a[2]), "r"(a[3]), "r"(lb), "n"(OB), "r"(one));
}
__host__ __device__ constexpr int koff(int kk, int chunk) { return ((kk >> 2) * chunk + (kk & 3) * 32) >> 4; }

__device__ __forceinline__ void stsm4(uint32_t addr, const uint4& v) {
    asm volatile("stmatrix.sync.aligned.m8n8.x4.shared.b16 [%0], {%1, %2, %3, %4};" ::"r"(addr), "r"(v.x), "r"(v.y), "r"(v.z), "r"(v.w) : "memory");
}
__device__ __forceinline__ void bulk_wait_read() {
    asm volatile("cp.async.bulk.wait_group.read 0;" ::: "memory");
}
__device__ __forceinline__ uint32_t stage_addr(uint32_t slot, uint32_t l) { return slot + (l & 7) * 128 + ((((l >> 3) & 3) ^ (l & 7)) << 4); }
__device__ __forceinline__ uint32_t tid_opaque() { return __shfl_sync(0xffffffffu, tid_now(), tid_now() & 31); }
template <int R> __device__ __forceinline__ void stage_round(const uint4 (&h)[12], uint32_t sa) {
#pragma unroll
    for (int i = 0; i < 2; i++) {
        const int r = (2 * R + i) / 3, c = (2 * R + i) % 3;
        stsm4(sa + i * 1024, h[4 * c + r]);
        stsm4((sa ^ 64) + i * 1024, h[4 * c + 2 + r]);
    }
}
__device__ __forceinline__ void stage_fence() {
    asm volatile("fence.proxy.async.shared::cta;" ::: "memory");
    __syncwarp();
}
template <int R> __device__ __forceinline__ void send_round(uint32_t slot, const CUtensorMap* tm, int col, int row) {
    asm volatile("{\n.reg .pred p;\nelect.sync _|p, 0xffffffff;\n"
                 "@p cp.async.bulk.tensor.4d.global.shared::cta.bulk_group [%0, {%2, %3, %4, %5}], [%1];\n"
                 "@p cp.async.bulk.commit_group;\n}\n"
                 ::"l"(tm + (R == 1)), "r"(slot), "r"(0), "r"(col), "r"(row + (R == 2)), "r"((int)(R == 2)) : "memory");
}
template <int R> __device__ __forceinline__ void store_round(const uint4 (&h)[12], uint32_t slot, const CUtensorMap* tm, int col, int row) {
    stage_round<R>(h, stage_addr(slot, tid_now()));
    stage_fence();
    send_round<R>(slot, tm, col, row);
}
__device__ __forceinline__ uint32_t warp4_uniform() { return __reduce_or_sync(0xffffffffu, (tid_now() >> 5) & 3); }
struct OutMaps { CUtensorMap m[2]; };
__host__ __device__ constexpr uint32_t bar_m(int c) { return kSmemBase + kOffBar + 32 + 8 * c; }
__device__ __forceinline__ void m_load(const Scratch* sc, int c, uint32_t par) {
    mbar_expect_tx(bar_m(c), 24576);
    bulk_load(kSmemBase + kOffWm + c * 24576, sc->img[par][0] + c * 1536, 24576, bar_m(c));
}
__device__ __forceinline__ bool m_agree(uint32_t ok) {
    uint32_t all;
    asm volatile("{\n.reg .pred p, q;\nsetp.ne.u32 p, %1, 0;\nbar.red.and.pred q, 7, 256, p;\nselp.b32 %0, 1, 0, q;\n}\n" : "=r"(all) : "r"(ok) : "memory");
    return all != 0;
}
__device__ __forceinline__ void m_check(const Scratch* sc, uint32_t par) {
    for (uint32_t round = 0;; round++) {
        uint32_t m = ~0u;
#pragma unroll 1
        for (int c = 0; c < 3; c++) {
            mbar_wait(bar_m(c), round & 1);
#pragma unroll
            for (int j = 0; j < 6; j++) {
                uint32_t v;
                asm volatile("ld.volatile.shared.b32 %0, [%1];" : "=r"(v)
                             : "r"(kSmemBase + kOffWm + c * 24576 + 4096 * j + (tid_now() & 127) * 32 + (tid_now() & 28)) : "memory");
                m = min(m, v);
            }
        }
        if (m_agree(m)) break;
        if (round > (1u << 20)) __trap();
        if (tid_now() == 128) {
            m_load(sc, 0, par); m_load(sc, 1, par); m_load(sc, 2, par);
        }
    }
}
constexpr uint32_t kBarV = kSmemBase + kOffBar + 56;
__device__ __forceinline__ void v_load(const Scratch* sc, uint32_t par) {
    mbar_expect_tx(kBarV, kWBytes);
#pragma unroll 1
    for (int c = 0; c < 3; c++) bulk_load(kSmemBase + kOffWv + c * 24576, sc->img[par][1] + c * 1536, 24576, kBarV);
}
__device__ __forceinline__ void v_check(const Scratch* sc, uint32_t par) {
    for (uint32_t round = 0;; round++) {
        mbar_wait(kBarV, round & 1);
        uint32_t m = ~0u;
#pragma unroll
        for (int j = 0; j < 18; j++) {
            uint32_t v;
            asm volatile("ld.volatile.shared.b32 %0, [%1];" : "=r"(v)
                         : "r"(kSmemBase + kOffWv + 4096 * j + (tid_now() & 127) * 32 + (tid_now() & 28)) : "memory");
            m = min(m, v);
        }
        uint32_t all;
        asm volatile("{\n.reg .pred p, q;\nsetp.ne.u32 p, %1, 0;\nbar.red.and.pred q, 14, 128, p;\nselp.b32 %0, 1, 0, q;\n}\n" : "=r"(all) : "r"(m) : "memory");
        if (all) break;
        if (round > (1u << 20)) __trap();
        if (tid_now() == 352) v_load(sc, par);
    }
}
__host__ __device__ constexpr uint32_t bar_x(int w, int c) { return kSmemBase + kOffBar + 128 + 32 * w + 8 * c; }
template <int K> struct Gemm1 {
    static __device__ __forceinline__ void run(float (&d)[96], uint32_t lx, uint32_t lw, bool very_first, uint32_t st) {
        if constexpr (K > 0) Gemm1<K - 1>::run(d, lx, lw, very_first, st);
        if constexpr (K == 0 || K == 4 || K == 8) {
            if constexpr (K == 0) {
                if (very_first) mbar_wait(bar_m(0), (st & kRound) != 0);
            } else if (st & kFirst) {
                mbar_wait(bar_x(0, K / 4) + 32 * (tid_now() >> 7), 0);
                if (very_first) mbar_wait(bar_m(K / 4), (st & kRound) != 0);
            }
            wg_fence();
        }
        wg192_ss<K == 0, koff(K, 8192), koff(K, 24576)>(d, lx, lw);
    }
};
constexpr uint32_t kScAddr = kSmemBase + kOffBar + 96;
__device__ __forceinline__ void draw_ticket(uint32_t& ticket) {
    asm volatile("{\n.reg .pred p;\n.reg .b64 a;\nsetp.eq.u32 p, %1, 0;\nld.volatile.shared.u64 a, [%3];\n"
                 "@p atom.relaxed.gpu.global.inc.u32 %0, [a], %2;\n}\n"
                 : "+r"(ticket) : "r"(tid_now() & 127), "n"(kNWin - 1), "r"(kScAddr) : "memory");
}
template <int KK> struct Gemm2 { static __device__ __forceinline__ void run(float (&d)[32], const uint32_t* a, uint32_t lx, uint32_t lnk, uint32_t& st) {
    Gemm2<KK - 1>::run(d, a, lx, lnk, st); wg64_rs<KK == 0, 0, koff(KK, 8192)>(d, a + 4 * KK, lx);
    if constexpr (KK == 9) {
        __syncwarp();
        bulk_wait_read();
        baton_pass(lnk, st);
    } } };
template <> struct Gemm2<-1> { static __device__ __forceinline__ void run(float (&)[32], const uint32_t*, uint32_t, uint32_t, uint32_t&) {} };
template <int KK> struct Gemm3 { static __device__ __forceinline__ void run(float (&d)[96], const uint32_t* a, uint32_t lxt) {
    Gemm3<KK - 1>::run(d, a, lxt); wg192_rs<KK == 0, 1, KK * (2048 >> 4)>(d, a + 4 * KK, lxt); } };
template <> struct Gemm3<-1> { static __device__ __forceinline__ void run(float (&)[96], const uint32_t*, uint32_t) {} };
template <int K0, int KK> struct Gemm4 { static __device__ __forceinline__ void run(float (&d)[96], const uint32_t* a, uint32_t lw) {
    if constexpr (KK > K0) Gemm4<K0, KK - 1>::run(d, a, lw);
    wg192_rs<KK == 0, 0, koff(KK, 24576)>(d, a + 4 * KK, lw); } };

template <int C, int KK> struct Gemm3s { static __device__ __forceinline__ void run(float (&d)[32], const uint32_t* a, uint32_t lxt) {
    if constexpr (KK > 0) Gemm3s<C, KK - 1>::run(d, a, lxt);
    wg64_rs<KK == 0, 1, (C * 8192 + KK * 2048) / 16>(d, a + 4 * KK, lxt); } };
template <int C, int K0, int KK> struct Gemm4s { static __device__ __forceinline__ void run(float (&d)[32], const uint32_t* a, uint32_t lw, uint32_t one) {
    if constexpr (KK > K0) Gemm4s<C, K0, KK - 1>::run(d, a, lw, one);
    if constexpr (KK == 0) wg64_rs_reuse<C * 8192 / 16>(d, a, lw, one);
    else wg64_rs<false, 0, koff(KK, 24576) + C * 8192 / 16>(d, a + 4 * KK, lw); } };

__device__ __forceinline__ uint32_t pack_bf16(float lo, float hi) {
    uint32_t r;
    asm("cvt.rn.bf16x2.f32 %0, %1, %2;" : "=r"(r) : "f"(hi), "f"(lo));
    return r;
}
__device__ __forceinline__ float ex2(float x) {
    float r;
    asm("ex2.approx.ftz.f32 %0, %1;" : "=f"(r) : "f"(x));
    return r;
}
__device__ __forceinline__ float rcp(float x) {
    float r;
    asm("rcp.approx.ftz.f32 %0, %1;" : "=f"(r) : "f"(x));
    return r;
}
__device__ __forceinline__ void mma16816(float (&c)[4], uint32_t a0, uint32_t a1, uint32_t a2, uint32_t a3,
                                         uint32_t b0, uint32_t b1) {
    asm volatile("mma.sync.aligned.m16n8k16.row.col.f32.bf16.bf16.f32 {%0,%1,%2,%3}, {%4,%5,%6,%7}, {%8,%9}, {%0,%1,%2,%3};"
                 : "+f"(c[0]), "+f"(c[1]), "+f"(c[2]), "+f"(c[3])
                 : "r"(a0), "r"(a1), "r"(a2), "r"(a3), "r"(b0), "r"(b1));
}

struct FoldRegs { uint4 B0[6], B1[6]; uint32_t A[48]; };

__device__ __forceinline__ void st_relaxed64(void* p, uint32_t a, uint32_t b, uint32_t on) {
    asm volatile("{\n.reg .pred q;\nsetp.ne.u32 q, %3, 0;\n@q st.relaxed.gpu.global.v2.b32 [%0], {%1, %2};\n}\n" ::"l"(p), "r"(a), "r"(b), "r"(on) : "memory");
}
__device__ __forceinline__ uint32_t pack_nonzero(float lo, float hi) { const uint32_t v = pack_bf16(lo, hi); return v != 0 ? v : 0x80000000u; }
__device__ __forceinline__ void fold_store(char* img, uint32_t* cnt, uint32_t epoch, uint32_t on, int n_lo, int n_hi, int k0, int lane, const float (&c0)[4], const float (&c1)[4]) {
    const int q = lane & 3;
    const int u = ((k0 & 63) >> 3) + (q >> 1);
    const int base = (k0 >> 6) * 24576 + (q & 1) * 8;
    char* p_lo = img + (base + n_lo * 128 + ((u ^ (n_lo & 7)) << 4));
    char* p_hi = img + (base + n_hi * 128 + ((u ^ (n_hi & 7)) << 4));
    const uint32_t v0 = pack_nonzero(c0[0], c0[1]);
    const uint32_t par = (epoch & 1) | (v0 & (gridDim.y - 1));
    st_relaxed64(p_lo + par * (2 * kWBytes), v0, pack_nonzero(c1[0], c1[1]), on);
    st_relaxed64(p_hi + par * (2 * kWBytes), pack_nonzero(c0[2], c0[3]), pack_nonzero(c1[2], c1[3]), on);
    asm volatile("{\n.reg .pred q;\nsetp.ne.u32 q, %1, 0;\n@q red.relaxed.gpu.global.inc.u32 [%0], 0xffffffff;\n}\n" ::"l"(cnt), "r"(lane == 0 ? on : 0u) : "memory");
    st_relaxed64(p_lo + (par ^ 1) * (2 * kWBytes), 0, 0, on);
    st_relaxed64(p_hi + (par ^ 1) * (2 * kWBytes), 0, 0, on);
}
__device__ __forceinline__ void fold_load_qk(FoldRegs& r, const __nv_bfloat16* __restrict__ wqkv, int tile, int lane) {
    const int g = lane >> 2, q = lane & 3;
    const int n0 = (tile / 12) * 16, k0 = (tile % 12) * 16;
    const int kb = k0 + 4 * (g >> 1) + (g & 1);
    const uint4* pa0 = reinterpret_cast<const uint4*>(wqkv + (size_t)(n0 + g) * 576 + 192 + 8 * q);
    const uint4* pa1 = reinterpret_cast<const uint4*>(wqkv + (size_t)(n0 + g + 8) * 576 + 192 + 8 * q);
    const uint4* pb0 = reinterpret_cast<const uint4*>(wqkv + (size_t)kb * 576 + 8 * q);
    const uint4* pb1 = reinterpret_cast<const uint4*>(wqkv + (size_t)(kb + 2) * 576 + 8 * q);
#pragma unroll
    for (int j = 0; j < 6; j++) {
        const uint4 lo = __ldg(pa0 + 4 * j), hi = __ldg(pa1 + 4 * j);
        r.A[8 * j + 0] = lo.x; r.A[8 * j + 1] = hi.x; r.A[8 * j + 2] = lo.y; r.A[8 * j + 3] = hi.y;
        r.A[8 * j + 4] = lo.z; r.A[8 * j + 5] = hi.z; r.A[8 * j + 6] = lo.w; r.A[8 * j + 7] = hi.w;
        r.B0[j] = __ldg(pb0 + 4 * j);
        r.B1[j] = __ldg(pb1 + 4 * j);
    }
}
__device__ __forceinline__ void fold_load_vo(FoldRegs& r, const __nv_bfloat16* __restrict__ wqkv, const __nv_bfloat16* __restrict__ wo,
                                             int tile, int lane) {
    const int g = lane >> 2, q = lane & 3;
    const int ch0 = (tile / 12) * 16 + 2 * g;
    const int k0 = (tile % 12) * 16;
    const int kb = k0 + 4 * (g >> 1) + (g & 1);
    const uint4* pb0 = reinterpret_cast<const uint4*>(wqkv + (size_t)kb * 576 + 384 + 8 * q);
    const uint4* pb1 = reinterpret_cast<const uint4*>(wqkv + (size_t)(kb + 2) * 576 + 384 + 8 * q);
    const uint32_t* pw = reinterpret_cast<const uint32_t*>(wo + (size_t)(8 * q) * kC + ch0);
#pragma unroll
    for (int j = 0; j < 6; j++) {
        r.B0[j] = __ldg(pb0 + 4 * j);
        r.B1[j] = __ldg(pb1 + 4 * j);
#pragma unroll
        for (int i = 0; i < 8; i++) r.A[8 * j + i] = __ldg(pw + (32 * j + i) * (kC / 2));
    }
}
template <bool kVO>
__device__ __forceinline__ void fold_compute_store(FoldRegs& r, Scratch* sc, int tile, int lane, uint32_t epoch, uint32_t on) {
    const int g = lane >> 2;
    float c0[4] = {0.f, 0.f, 0.f, 0.f}, c1[4] = {0.f, 0.f, 0.f, 0.f}, c2[4] = {0.f, 0.f, 0.f, 0.f}, c3[4] = {0.f, 0.f, 0.f, 0.f};
#pragma unroll
    for (int j = 0; j < 6; j++) {
        uint32_t a[8];
        if constexpr (kVO) {
#pragma unroll
            for (int i = 0; i < 4; i++) {
                a[2 * i]     = __byte_perm(r.A[8 * j + 2 * i], r.A[8 * j + 2 * i + 1], 0x5410);
                a[2 * i + 1] = __byte_perm(r.A[8 * j + 2 * i], r.A[8 * j + 2 * i + 1], 0x7632);
            }
        } else {
#pragma unroll
            for (int i = 0; i < 8; i++) asm volatile("prmt.b32 %0, %1, 0, 0x3210;" : "=r"(a[i]) : "r"(r.A[8 * j + i]));
        }
        mma16816(c0, a[0], a[1], a[2], a[3], r.B0[j].x, r.B0[j].y);
        mma16816(c1, a[0], a[1], a[2], a[3], r.B1[j].x, r.B1[j].y);
        mma16816(c2, a[4], a[5], a[6], a[7], r.B0[j].z, r.B0[j].w);
        mma16816(c3, a[4], a[5], a[6], a[7], r.B1[j].z, r.B1[j].w);
    }
#pragma unroll
    for (int i = 0; i < 4; i++) { c0[i] += c2[i]; c1[i] += c3[i]; }
    const int k0 = (tile % 12) * 16;
    if constexpr (kVO) {
        const int n = (tile / 12) * 16 + 2 * g;
        fold_store(reinterpret_cast<char*>(sc->img[0][1]), sc->cnt_v, epoch, on, n, n + 1, k0, lane, c0, c1);
    } else {
        const int n0 = (tile / 12) * 16;
        fold_store(reinterpret_cast<char*>(sc->img[0][0]), sc->cnt_m, epoch, on, n0 + g, n0 + g + 8, k0, lane, c0, c1);
    }
}

__device__ __forceinline__ void prefetch_x(const CUtensorMap* tm, int win) {
    const int wh = win >> 6, ww = win & 63;
    asm volatile("cp.async.bulk.prefetch.tensor.3d.L2.global.tile [%0, {%1, %2, %3}];"
                 ::"l"(tm), "r"(0), "r"(ww * 8), "r"(wh * 8) : "memory");
}

__device__ __forceinline__ void reset_for_next_launch() {
    Scratch* q;
    asm volatile("ld.volatile.shared.u64 %0, [%1];" : "=l"(q) : "r"(kScAddr) : "memory");
    q->cnt_v[0] = 0; q->cnt_m[0] = 0; atomicAdd(q->epoch, 1);
}
__device__ __forceinline__ void finish_alone(uint32_t dXt, uint32_t dWv, int win) {
    uint32_t pa[16];
#pragma unroll
    for (int j = 0; j < 4; j++)
        asm volatile("ld.volatile.shared.v4.b32 {%0, %1, %2, %3}, [%4];" : "=r"(pa[4 * j]), "=r"(pa[4 * j + 1]), "=r"(pa[4 * j + 2]), "=r"(pa[4 * j + 3])
                     : "r"(kSmemBase + kOffStage + j * 2048 + (tid_now() & 127) * 16) : "memory");
    const uint32_t one = gridDim.y;
    float u0[32], u1[32], u2[32];
    float (&o0)[32] = u0, (&o1)[32] = u2, (&o2)[32] = u0;
    uint32_t fa[48];
    uint4 h[4];
    const float nz = __uint_as_float(one << 31);
    auto pack_a = [&](float (&u)[32], int c) {
        fence_regs(u);
#pragma unroll
        for (int i = 0; i < 16; i++) {
            fa[16 * c + i] = pack_bf16(c != 1 ? u[2 * i] + nz : u[2 * i], u[2 * i + 1]);
            asm volatile("" : "+r"(fa[16 * c + i])::"memory");
        }
        wg_fence();
    };
    auto pack_o = [&](float (&o)[32], bool first) {
        fence_regs(o);
        auto pk = [&](int i) { return pack_bf16(o[i], first ? o[i + 1] + nz : o[i + 1]); };
#pragma unroll
        for (int i = 0; i < 4; i++) {
            const int b = 16 * (i & 1) + 2 * (i >> 1);
            h[i] = make_uint4(pk(b), pk(b + 4), pk(b + 8), pk(b + 12));
        }
#pragma unroll
        for (int i = 0; i < 4; i++) asm volatile("" : "+r"(h[i].x), "+r"(h[i].y), "+r"(h[i].z), "+r"(h[i].w)::"memory");
    };
    wg_fence();
    Gemm3s<0, 3>::run(u0, pa, dXt); wg_commit();
    Gemm3s<1, 3>::run(u1, pa, dXt); wg_commit();
    Gemm3s<2, 3>::run(u2, pa, dXt); wg_commit();
    const uint32_t t = tid_now(), slot = kSmemBase + kOffStage + (t & 96) * 64;
    const uint32_t sa = stage_addr(slot, t);
    const uint32_t tok = (t >> 3) & 3, j = t & 7, la = slot + tok * 128 + ((j ^ tok) << 4);
    char* out;
    asm volatile("ld.volatile.shared.u64 %0, [%1];" : "=l"(out) : "r"(kScAddr + 8) : "memory");
    out += (((win >> 6) * 8 + ((t >> 4) & 6)) * kHW + (win & 63) * 8 + tok) * (kC * 2) + j * 16;
    uint4 v[4];
    auto S = [&](int i) { stsm4((sa ^ (i & 1) * 64) + (i >> 1) * 1024, h[i]); };
    auto L = [&](int i) {
        asm volatile("ld.volatile.shared.v4.b32 {%0, %1, %2, %3}, [%4];" : "=r"(v[i].x), "=r"(v[i].y), "=r"(v[i].z), "=r"(v[i].w)
                     : "r"((la ^ (i & 1) * 64) + i * 512) : "memory");
    };
    auto G = [&](int c, int i) {
        asm volatile("st.global.v4.b32 [%0], {%1, %2, %3, %4};"
                     ::"l"(out + ((i >> 1) * kHW + 4 * (i & 1)) * (kC * 2) + c * 128), "r"(v[i].x), "r"(v[i].y), "r"(v[i].z), "r"(v[i].w) : "memory");
    };
#define W(C, K0, K1, O) Gemm4s<C, K0, K1>::run(O, fa, dWv, one)
#define PIN __syncwarp()
    wg_wait2(); pack_a(u0, 0);
    asm volatile("bar.sync %0, 128;" ::"r"((tid_now() >> 7) + 1) : "memory");
    W(0, 0, 3, o0); wg_commit();
    wg_wait2(); pack_a(u1, 1);
    W(0, 4, 7, o0); wg_commit();
    wg_wait2(); pack_a(u2, 2);
    W(0, 8, 11, o0); wg_commit();
    W(1, 0, 5, o1); wg_commit();
    wg_wait1(); pack_o(o0, true);
    W(1, 6, 6, o1); S(0); W(1, 7, 7, o1); S(1); W(1, 8, 8, o1); S(2); W(1, 9, 9, o1); S(3); W(1, 10, 10, o1); PIN; L(0); W(1, 11, 11, o1); wg_commit(); L(1);
    wg_fence();
    W(2, 0, 0, o2); L(2); W(2, 1, 1, o2); L(3); W(2, 2, 2, o2); PIN; G(0, 0); PIN; W(2, 3, 3, o2); G(0, 1); PIN; W(2, 4, 4, o2); G(0, 2); PIN; W(2, 5, 5, o2); wg_commit(); G(0, 3);
    PIN;
    wg_wait1(); pack_o(o1, false);
    W(2, 6, 6, o2); S(0); W(2, 7, 7, o2); S(1); W(2, 8, 8, o2); S(2); W(2, 9, 9, o2); S(3); W(2, 10, 11, o2); wg_commit();
    wg_wait1();
    PIN; L(0); L(1); L(2); L(3); G(1, 0); G(1, 1); G(1, 2); G(1, 3);
    PIN;
    wg_wait0(); pack_o(o2, false);
    fence_regs(fa);
    S(0); S(1); S(2); S(3); PIN; L(0); L(1); L(2); L(3); G(2, 0); G(2, 1); G(2, 2); G(2, 3);
#undef W
#undef PIN
}

__global__ void __launch_bounds__(kThreads, 1)
swin_attn_kernel(const __nv_bfloat16* __restrict__ wqkv, const __nv_bfloat16* __restrict__ wo, Scratch* __restrict__ sc, void* out,
                 const __grid_constant__ OutMaps tmo, const __grid_constant__ CUtensorMap tmx, const __grid_constant__ CUtensorMap tmp, const __grid_constant__ CUtensorMap tmc) {
    extern __shared__ uint8_t smem_raw[];
    constexpr uint32_t sbase = kSmemBase;
    if (smem_u32(smem_raw) != kSmemBase) __trap();
    const int tid = threadIdx.x, lane = tid & 31;
    const uint32_t warpu = __reduce_or_sync(0xffffffffu, (uint32_t)tid >> 5), wgu = warpu >> 2;
    const int warp = (int)warpu, wg = (int)wgu;
    const int G = gridDim.x;

    const int ftile = blockIdx.x + (warp & 1) * G;
    FoldRegs fq;
#pragma unroll
    for (int j = 0; j < 6; j++) {
        asm volatile("" : "=r"(fq.B0[j].x), "=r"(fq.B0[j].y), "=r"(fq.B0[j].z), "=r"(fq.B0[j].w));
        asm volatile("" : "=r"(fq.B1[j].x), "=r"(fq.B1[j].y), "=r"(fq.B1[j].z), "=r"(fq.B1[j].w));
    }
#pragma unroll
    for (int j = 0; j < 48; j++) asm volatile("" : "=r"(fq.A[j]));
    uint32_t epoch;
    asm volatile("ld.relaxed.gpu.global.u32 %0, [%1];" : "=r"(epoch) : "l"(sc->epoch) : "memory");
    if (warp < 2 && ftile < kTiles) fold_load_qk(fq, wqkv, ftile, lane);
    if (warp == 3) {
        const uint32_t i = blockIdx.x + G * (lane & 15);
        const char* p = lane < 16 ? (const char*)wo + i * 128 : (const char*)wqkv + i * 128 + (i / 3 + 1) * 768;
        if (i < 576) asm volatile("prefetch.global.L2 [%0];" ::"l"(p) : "memory");
    }
    if (warp == 10) {
        if (lane == 0) {
#pragma unroll
            for (int w = 0; w < kNWG; w++) {
                mbar_init(sbase + kOffBar + 8 * w, 1);
#pragma unroll
                for (int c = 0; c < 3; c++) mbar_init(bar_x(w, c), 1);
            }
            asm volatile("fence.mbarrier_init.release.cluster;" ::: "memory");
        }
        __syncwarp();
        asm volatile("bar.arrive 11, 384;" ::: "memory");
        if (lane == 0) {
            const uint32_t t0 = (uint32_t)clock64() + kPaceStart + ((blockIdx.x * 37) & 63) * kPaceSpread / 64;
#pragma unroll 1
            for (int i = 0; i <= 3 * kNWG; i++) {
                while ((int)((uint32_t)clock64() - t0) < (i < 3 ? i * kPaceStep0 : kPaceMid + (i - 3) * kPaceStep)) {}
                const int w = i / 3, c = i % 3;
                if (w < kNWG) {
                    mbar_expect_tx(bar_x(w, c), 8192);
                    tma_load_x_chunk(sbase + kOffX + w * kXBytes + c * 8192, &tmc, bar_x(w, c), w * G + blockIdx.x, c);
                } else {
                    prefetch_x(&tmp, kNWG * G + blockIdx.x);
                }
            }
        }
    }
    if (warp < 3) {
        for (int t = ftile;;) {
            const bool on = warp < 2 && t < kTiles;
            fold_compute_store<false>(fq, sc, t, lane, epoch, on);
            t += 2 * G;
            if (__builtin_expect(warp == 2 || t >= kTiles, 1)) break;
            fold_load_qk(fq, wqkv, t, lane);
        }
    }
    if (warp < 4) {
        asm volatile("bar.sync 11, 384;" ::: "memory");
    } else if (warp == 4) {
        if (lane == 0) {
            set_link(0, 9); set_link(1, 8); set_link(2, 8);
            asm volatile("st.shared.v2.u64 [%0], {%1, %2};" ::"r"(kScAddr), "l"(sc), "l"(out) : "memory");
            mbar_init(bar_m(0), 1);
            mbar_init(bar_m(1), 1);
            mbar_init(bar_m(2), 1);
            asm volatile("fence.mbarrier_init.release.cluster;" ::: "memory");
        }
        __syncwarp();
        asm volatile("bar.arrive 12, 128;" ::: "memory");
        uint32_t v;
        asm volatile("ld.relaxed.gpu.global.u32 %0, [%1];" : "=r"(v) : "l"(sc->cnt_m) : "memory");
        asm volatile("bar.sync 11, 384;" ::: "memory");
        { const uint32_t t0 = (uint32_t)clock64(); while ((uint32_t)clock64() - t0 < kPollDelay) {} }
        if (lane == 0) {
            uint32_t spins = 0;
            while (v < kMqkHint) {
                asm volatile("ld.relaxed.gpu.global.u32 %0, [%1];" : "=r"(v) : "l"(sc->cnt_m) : "memory");
                if (++spins > (1u << 22)) __trap();
            }
            const uint32_t par = epoch & 1;
            m_load(sc, 0, par); m_load(sc, 1, par); m_load(sc, 2, par);
        }
    } else if (warp == 11) {
        if (lane == 0) {
            mbar_init(kBarV, 1);
            asm volatile("fence.mbarrier_init.release.cluster;" ::: "memory");
        }
        __syncwarp();
        asm volatile("bar.sync 11, 384;" ::: "memory");
        if (lane == 0) {
            uint32_t v, spins = 0;
            do {
                asm volatile("ld.relaxed.gpu.global.u32 %0, [%1];" : "=r"(v) : "l"(sc->cnt_v) : "memory");
                if (++spins > (1u << 22)) __trap();
            } while (v < kTiles);
            uint32_t ok = 0, n = 0;
            while (!ok && ++n < 64)
                asm volatile("{\n.reg .pred p;\nmbarrier.try_wait.parity.shared::cta.b64 p, [%1], 0;\nselp.b32 %0, 1, 0, p;\n}\n" : "=r"(ok) : "r"(bar_m(2)) : "memory");
            v_load(sc, epoch & 1);
        }
    } else if (warp == 10) {
    } else if (warp >= 8) {
        asm volatile("bar.arrive 11, 384;" ::: "memory");
        if (warp == 9) { const uint32_t t0 = (uint32_t)clock64(); while ((uint32_t)clock64() - t0 < kWvoDelay) {} }
        FoldRegs fr;
        for (int t = G - 1 - blockIdx.x + (warp & 1) * G; t < kTiles; t += 2 * G) {
            fold_load_vo(fr, wqkv, wo, t, lane);
            fold_compute_store<true>(fr, sc, t, lane, epoch, 1);
        }
    } else {
        asm volatile("bar.arrive 11, 384;" ::: "memory");
        if (lane == 0) asm volatile("prefetch.tensormap [%0];" ::"l"(warp == 5 ? &tmo.m[0] : warp == 6 ? &tmo.m[1] : &tmx) : "memory");
        asm volatile("bar.sync 12, 128;" ::: "memory");
    }
    __syncwarp();
    if (wg == 1) m_check(sc, epoch & 1);
    uint4 hv[12];
#pragma unroll
    for (int a = 0; a < 12; a++) asm volatile("" : "=r"(hv[a].x), "=r"(hv[a].y), "=r"(hv[a].z), "=r"(hv[a].w));

    constexpr uint32_t dWm = ((sbase + kOffWm) >> 4) | (1u << 16);
    constexpr uint32_t dWv = ((sbase + kOffWv) >> 4) | (1u << 16);
    const float cs = 0.07216878364870322f * 1.4426950408889634f;
    if (wg == 2) {
        asm volatile("bar.sync 13, 128;" ::: "memory");
        v_check(sc, epoch & 1);
    }
    mbar_wait(bar_x(wg, 0), 0);

    uint32_t st = (uint32_t)(wg * G + blockIdx.x) << 17 | kFirst | kPhase | (wg == 0 ? kSolo | kVeryFirst : 0);

    while (true) {
        float acc[96];
        uint32_t fa[48];
        const uint32_t dX = ((sbase + kOffX + wg_uniform() * kXBytes) >> 4) | (1u << 16);
        uint32_t ticket = 0;
        uint32_t lnk = baton_wait(st, 0);
        while (true) {
            const bool very_first = st & kVeryFirst;
            Gemm1<11>::run(acc, dX, dWm, very_first, st);
            wg_commit();
            if (!very_first) { baton_pass(lnk, st); break; }
            wg_wait0();
            if (m_agree(1)) break;
            st ^= kRound;
        }
        draw_ticket(ticket);
        if (!(st & kFirst)) {
            const uint32_t w4 = warp4_uniform();
            const uint32_t slot = sbase + kOffStage + w4 * 2048;
            const int col = (st_out(st) & 63) * 8, row = (st_out(st) >> 6) * 8 + 2 * w4;
            store_round<0>(hv, slot, tmo.m, col, row);
            bulk_wait_read();
            __syncwarp();
            store_round<1>(hv, slot, tmo.m, col, row);
            bulk_wait_read();
            __syncwarp();
            store_round<2>(hv, slot, tmo.m, col, row);
        }
        static_assert(kPfInit == 2, "one start-up prefetch in the prologue, one here");
        if ((st & kFirst) && tid_now() == 128) prefetch_x(&tmp, (kNWG + (tid_now() >> 7)) * gridDim.x + blockIdx.x);
        __syncwarp();
        wg_wait0();
        fence_regs(acc);
#pragma unroll
        for (int i = 0; i < 48; i++) fa[i] = pack_bf16(acc[2 * i], acc[2 * i + 1]);

        float s[32];
        fence_regs(fa);
        lnk = baton_wait(st, fa[47]);
        wg_fence();
        Gemm2<11>::run(s, fa, dX, lnk, st);
        wg_commit();
        wg_wait0();
        fence_regs(s);
        fence_regs(fa);

        uint32_t pa[16];
        {
            float a0[8], a1[8];
#pragma unroll
            for (int j = 0; j < 8; j++) { a0[j] = fmaxf(s[4 * j], s[4 * j + 1]); a1[j] = fmaxf(s[4 * j + 2], s[4 * j + 3]); }
#pragma unroll
            for (int d = 4; d > 0; d >>= 1)
#pragma unroll
                for (int j = 0; j < d; j++) { a0[j] = fmaxf(a0[j], a0[j + d]); a1[j] = fmaxf(a1[j], a1[j + d]); }
            float m0 = a0[0], m1 = a1[0];
            m0 = fmaxf(m0, __shfl_xor_sync(0xffffffffu, m0, 1));
            m1 = fmaxf(m1, __shfl_xor_sync(0xffffffffu, m1, 1));
            m0 = fmaxf(m0, __shfl_xor_sync(0xffffffffu, m0, 2));
            m1 = fmaxf(m1, __shfl_xor_sync(0xffffffffu, m1, 2));
            m0 *= cs; m1 *= cs;
            float l0 = 0.f, l1 = 0.f;
#pragma unroll
            for (int j = 0; j < 8; j++) {
                s[4 * j]     = ex2(fmaf(s[4 * j], cs, -m0));
                s[4 * j + 1] = ex2(fmaf(s[4 * j + 1], cs, -m0));
                s[4 * j + 2] = ex2(fmaf(s[4 * j + 2], cs, -m1));
                s[4 * j + 3] = ex2(fmaf(s[4 * j + 3], cs, -m1));
                l0 += s[4 * j] + s[4 * j + 1];
                l1 += s[4 * j + 2] + s[4 * j + 3];
            }
            l0 += __shfl_xor_sync(0xffffffffu, l0, 1);
            l1 += __shfl_xor_sync(0xffffffffu, l1, 1);
            l0 += __shfl_xor_sync(0xffffffffu, l0, 2);
            l1 += __shfl_xor_sync(0xffffffffu, l1, 2);
            const float r0 = rcp(l0), r1 = rcp(l1);
#pragma unroll
            for (int j = 0; j < 8; j++) {
                pa[2 * j]     = pack_bf16(s[4 * j] * r0, s[4 * j + 1] * r0);
                pa[2 * j + 1] = pack_bf16(s[4 * j + 2] * r1, s[4 * j + 3] * r1);
            }
        }

        fence_regs(pa);
        if ((tid_now() & 127) == 0)
            asm volatile("st.volatile.shared.u32 [%0], %1;" ::"r"(kLink + 4 + 8 * (tid_now() >> 7)), "r"(kNWG * gridDim.x + ticket) : "memory");
        uint32_t pub;
        lnk = baton_wait_pub(st, pa[15], pub);
        if ((st & kFirst) && tid_now() == 0) set_link(1, 10);
        const bool alone = lnk == (tid_now() >> 7) + 8 && pub >= kNWin;
        asm volatile("{\n.reg .pred p;\nsetp.ne.u32 p, %16, 0;\n"
                     "@p st.volatile.shared.v4.b32 [%17], {%0, %1, %2, %3};\n@p st.volatile.shared.v4.b32 [%17 + 2048], {%4, %5, %6, %7};\n"
                     "@p st.volatile.shared.v4.b32 [%17 + 4096], {%8, %9, %10, %11};\n@p st.volatile.shared.v4.b32 [%17 + 6144], {%12, %13, %14, %15};\n}\n"
                     :: "r"(pa[0]), "r"(pa[1]), "r"(pa[2]), "r"(pa[3]), "r"(pa[4]), "r"(pa[5]), "r"(pa[6]), "r"(pa[7]),
                        "r"(pa[8]), "r"(pa[9]), "r"(pa[10]), "r"(pa[11]), "r"(pa[12]), "r"(pa[13]), "r"(pa[14]), "r"(pa[15]),
                        "r"((uint32_t)alone), "r"(sbase + kOffStage + (tid_now() & 127) * 16) : "memory");
        if (alone) {
            if (ticket == kNWin - 1) reset_for_next_launch();
            __syncwarp();
            finish_alone(dX + (((8192u >> 4) - 1) << 16), dWv, st_win(st));
            return;
        }
        wg_fence();
        Gemm3<3>::run(acc, pa, dX + (((8192u >> 4) - 1) << 16));
        wg_commit();
        baton_pass(lnk, st);
        const int nxt = (int)__reduce_or_sync(0xffffffffu, pub);
        wg_wait0();
        fence_regs(acc);
        fence_regs(pa);

        if (((tid_now() >> 5) & 3) == 0 && nxt < kNWin) {
            asm volatile("bar.sync %0, 128;" ::"r"((tid_now() >> 7) + 1) : "memory");
            if (elect_one()) {
                const uint32_t wgl = tid_now() >> 7;
                const uint32_t bar = sbase + kOffBar + 8 * wgl;
                mbar_expect_tx(bar, kXBytes);
                tma_load_x(sbase + kOffX + wgl * kXBytes, &tmx, bar, nxt);
            }
            __syncwarp();
        } else {
            asm volatile("bar.arrive %0, 128;" ::"r"((tid_now() >> 7) + 1) : "memory");
        }
#pragma unroll
        for (int i = 0; i < 48; i++) fa[i] = pack_bf16(acc[2 * i], acc[2 * i + 1]);

        asm volatile("st.volatile.shared.v4.b32 [%4], {%0, %1, %2, %3};"
                     :: "r"(fa[44]), "r"(fa[45]), "r"(fa[46]), "r"(fa[47]), "r"(sbase + kOffStash + (tid_now() & 127) * 16) : "memory");
        fence_regs(fa);
        if (((tid_now() >> 5) & 3) == 0 && nxt + kPfMin < kNWin) {
            if (elect_one()) {
                const int base = kNWG * (int)gridDim.x, t = nxt - base;
                const int hi = min(nxt + pf_lead(t), kNWin - 1);
                int lo = max(max(nxt - 1 + pf_lead(t - 1), nxt) + 1, base + kPfInit * (int)gridDim.x);
#pragma unroll 1
                for (; lo <= hi; lo++) prefetch_x(&tmp, lo);
            }
            __syncwarp();
        }
        lnk = baton_wait(st, fa[43]);
        if (nxt >= kNWin) {
            if ((tid_now() & 127) == 0) {
#pragma unroll
                for (int w = 0; w < kNWG; w++) {
                    uint32_t l;
                    asm volatile("ld.volatile.shared.u32 %0, [%1];" : "=r"(l) : "r"(kLink + 8 * w) : "memory");
                    if (l == (tid_now() >> 7) + 8) set_link(w, lnk);
                }
            }
        }
        __syncwarp();
        wg_fence();
        Gemm4<0, 1>::run(acc, fa, dWv);
        wg_commit();
        Gemm4<2, 10>::run(acc, fa, dWv);
        wg_commit();
        wg_wait1();
        uint32_t fl[4];
        asm volatile("ld.volatile.shared.v4.b32 {%0, %1, %2, %3}, [%4];"
                     : "=r"(fl[0]), "=r"(fl[1]), "=r"(fl[2]), "=r"(fl[3]) : "r"(sbase + kOffStash + (tid_now() & 127) * 16) : "memory");
        wg_fence();
        wg192_rs<false, 0, koff(11, 24576)>(acc, fl, dWv);
        wg_commit();
        baton_pass(lnk, st);
        if (nxt == kNWG * (int)gridDim.x + kNWin - 1 && (tid_now() & 127) == 0) reset_for_next_launch();
        __syncwarp();
        st = ((st ^ kPhase) & (kPhase | kSolo)) | st_win(st) << 4 | nxt << 17;
        uint32_t landed = 1;
        if (nxt < kNWin)
            asm volatile("{\n.reg .pred p;\nmbarrier.test_wait.parity.shared::cta.b64 p, [%1], %2;\nselp.b32 %0, 1, 0, p;\n}\n"
                         : "=r"(landed) : "r"(sbase + kOffBar + 8 * (tid_now() >> 7)), "r"(st & kPhase) : "memory");
        wg_wait0();
        fence_regs(acc);
        fence_regs(fa);
        fence_regs(fl);

#pragma unroll
        for (int a = 0; a < 6; a++)
#pragma unroll
            for (int r = 0; r < 2; r++)
                hv[2 * a + r] = make_uint4(pack_bf16(acc[16 * a + 2 * r], acc[16 * a + 2 * r + 1]), pack_bf16(acc[16 * a + 2 * r + 4], acc[16 * a + 2 * r + 5]),
                                           pack_bf16(acc[16 * a + 2 * r + 8], acc[16 * a + 2 * r + 9]), pack_bf16(acc[16 * a + 2 * r + 12], acc[16 * a + 2 * r + 13]));
        if (nxt >= kNWin) break;
        if (!landed) mbar_wait(sbase + kOffBar + 8 * (tid_now() >> 7), st & kPhase);
    }
    asm volatile("bar.sync %0, 128;" ::"r"((tid_now() >> 7) + 1) : "memory");
    {
        const uint32_t t = tid_opaque(), wu = __reduce_or_sync(0xffffffffu, t >> 5), w4 = wu & 3;
        const uint32_t slot = sbase + kOffX + wu * 6144, sa = stage_addr(slot, t);
        const int col = (st_out(st) & 63) * 8, row = (st_out(st) >> 6) * 8 + 2 * w4;
        stage_round<0>(hv, sa);
        stage_round<1>(hv, sa + 2048);
        stage_round<2>(hv, sa + 4096);
        stage_fence();
        send_round<0>(slot, tmo.m, col, row);
        send_round<1>(slot + 2048, tmo.m, col, row);
        send_round<2>(slot + 4096, tmo.m, col, row);
    }
    bulk_wait_read();
}

typedef CUresult (*EncodeTiledFn)(CUtensorMap*, CUtensorMapDataType, cuuint32_t, void*, const cuuint64_t*,
                                  const cuuint64_t*, const cuuint32_t*, const cuuint32_t*, CUtensorMapInterleave,
                                  CUtensorMapSwizzle, CUtensorMapL2promotion, CUtensorMapFloatOOBfill);

}

extern "C" void kernel_launch(void* const* d_in, const int* in_sizes, int n_in, void* d_out, int out_size) {
    (void)in_sizes; (void)n_in; (void)out_size;
    const __nv_bfloat16* x    = (const __nv_bfloat16*)d_in[0];
    const __nv_bfloat16* wqkv = (const __nv_bfloat16*)d_in[1];
    const __nv_bfloat16* wo   = (const __nv_bfloat16*)d_in[2];

    static EncodeTiledFn encode = nullptr;
    static int num_sms = 0;
    static Scratch* scratch = nullptr;
    if (!encode) {
        void* fn = nullptr;
        cudaDriverEntryPointQueryResult qr;
        cudaGetDriverEntryPoint("cuTensorMapEncodeTiled", &fn, cudaEnableDefault, &qr);
        encode = (EncodeTiledFn)fn;
        cudaGetSymbolAddress((void**)&scratch, g_scratch);
        int dev = 0;
        cudaGetDevice(&dev);
        cudaDeviceGetAttribute(&num_sms, cudaDevAttrMultiProcessorCount, dev);
        cudaFuncSetAttribute(swin_attn_kernel, cudaFuncAttributeMaxDynamicSharedMemorySize, kSmemBytes);
    }
    CUtensorMap tmx;
    const cuuint64_t gdim[4] = {64, (cuuint64_t)kHW, (cuuint64_t)kHW, 3};
    const cuuint64_t gstr[3] = {(cuuint64_t)kC * 2, (cuuint64_t)kHW * kC * 2, 128};
    const cuuint32_t box[4] = {64, 8, 8, 3};
    const cuuint32_t estr[4] = {1, 1, 1, 1};
    encode(&tmx, CU_TENSOR_MAP_DATA_TYPE_BFLOAT16, 4, (void*)x, gdim, gstr, box, estr, CU_TENSOR_MAP_INTERLEAVE_NONE,
           CU_TENSOR_MAP_SWIZZLE_128B, CU_TENSOR_MAP_L2_PROMOTION_NONE, CU_TENSOR_MAP_FLOAT_OOB_FILL_NONE);

    CUtensorMap tmp;
    const cuuint64_t pdim[3] = {(cuuint64_t)kC, (cuuint64_t)kHW, (cuuint64_t)kHW};
    const cuuint64_t pstr[2] = {(cuuint64_t)kC * 2, (cuuint64_t)kHW * kC * 2};
    const cuuint32_t pbox[3] = {(cuuint32_t)kC, 8, 8};
    encode(&tmp, CU_TENSOR_MAP_DATA_TYPE_BFLOAT16, 3, (void*)x, pdim, pstr, pbox, estr, CU_TENSOR_MAP_INTERLEAVE_NONE,
           CU_TENSOR_MAP_SWIZZLE_NONE, CU_TENSOR_MAP_L2_PROMOTION_NONE, CU_TENSOR_MAP_FLOAT_OOB_FILL_NONE);
    CUtensorMap tmc;
    const cuuint32_t boxc[4] = {64, 8, 8, 1};
    encode(&tmc, CU_TENSOR_MAP_DATA_TYPE_BFLOAT16, 4, (void*)x, gdim, gstr, boxc, estr, CU_TENSOR_MAP_INTERLEAVE_NONE,
           CU_TENSOR_MAP_SWIZZLE_128B, CU_TENSOR_MAP_L2_PROMOTION_NONE, CU_TENSOR_MAP_FLOAT_OOB_FILL_NONE);
    OutMaps tmo;
    const cuuint32_t boxo[4] = {64, 8, 1, 2};
    encode(&tmo.m[0], CU_TENSOR_MAP_DATA_TYPE_BFLOAT16, 4, d_out, gdim, gstr, boxo, estr, CU_TENSOR_MAP_INTERLEAVE_NONE,
           CU_TENSOR_MAP_SWIZZLE_128B, CU_TENSOR_MAP_L2_PROMOTION_NONE, CU_TENSOR_MAP_FLOAT_OOB_FILL_NONE);
    const cuuint64_t odim[4] = {64, (cuuint64_t)kHW, (cuuint64_t)kHW, 2};
    const cuuint64_t ostr[3] = {(cuuint64_t)kC * 2, (cuuint64_t)kHW * kC * 2, (cuuint64_t)kHW * kC * 2 - 256};
    encode(&tmo.m[1], CU_TENSOR_MAP_DATA_TYPE_BFLOAT16, 4, (char*)d_out + 256, odim, ostr, boxo, estr, CU_TENSOR_MAP_INTERLEAVE_NONE,
           CU_TENSOR_MAP_SWIZZLE_128B, CU_TENSOR_MAP_L2_PROMOTION_NONE, CU_TENSOR_MAP_FLOAT_OOB_FILL_NONE);
    swin_attn_kernel<<<num_sms, kThreads, kSmemBytes, cudaStreamPerThread>>>(wqkv, wo, scratch, d_out, tmo, tmx, tmp, tmc);
}
```

```cpp
#include <cuda_runtime.h>
#include <cuda_bf16.h>
#include <cuda.h>
#include <stdint.h>

namespace {

constexpr int kC      = 192;
constexpr int kHW     = 512;
constexpr int kNWin   = 4096;
constexpr int kSplit  = 7;
constexpr int kNItems = kNWin + 2 * kSplit;
constexpr int kEnd    = 0x4000;
constexpr int kXBytes = 64 * kC * 2;
constexpr int kWBytes = kC * kC * 2;
constexpr int kNWG    = 3;
constexpr int kThreads = kNWG * 128;
constexpr int kTiles  = 144;
constexpr int kPfInit = 2, kPfUp = 160, kPfPeak = 400, kPfHold = 800, kPfDown1 = 40, kPfBase2 = 300, kPfDown2 = 12, kPfMin = 140;
__device__ __forceinline__ int pf_lead(int t) {
    return min(min(kPfInit * (int)gridDim.x + ((t * kPfUp) >> 8), kPfPeak),
               max(max(kPfPeak - (((t - kPfHold) * kPfDown1) >> 8), kPfBase2 - ((t * kPfDown2) >> 8)), kPfMin));
}
constexpr int kEvictFrom = 3100;
constexpr int kPaceStart = 100, kPaceSpread = 500, kPaceStep0 = 750, kPaceMid = 2250, kPaceStep = 550;
constexpr uint32_t kMqkHint = 72;
constexpr uint32_t kPollDelay = 200;
constexpr uint32_t kWvoDelay = 1000;

constexpr int kOffWm  = 0;
constexpr int kOffWv  = kWBytes;
constexpr int kOffX   = 2 * kWBytes;
constexpr int kOffStage = kOffX + kNWG * kXBytes;
constexpr int kOffStash = kOffStage + 8192;
constexpr int kOffBar = kOffStash + 2048;
constexpr int kSmemBytes = kOffBar + 256;
constexpr uint32_t kSmemBase = 1024;

struct Scratch {
    uint32_t ticket[32];
    uint32_t epoch[32];
    uint32_t cnt_v[32];
    uint32_t cnt_m[32];
    uint4 img[2][2][kWBytes / 16];
};
__device__ __align__(128) Scratch g_scratch;

__device__ __forceinline__ uint32_t smem_u32(const void* p) { return (uint32_t)__cvta_generic_to_shared(p); }

__device__ __forceinline__ void mbar_init(uint32_t bar, uint32_t count) {
    asm volatile("mbarrier.init.shared::cta.b64 [%0], %1;" ::"r"(bar), "r"(count) : "memory");
}
__device__ __forceinline__ void mbar_expect_tx(uint32_t bar, uint32_t bytes) {
    asm volatile("mbarrier.arrive.expect_tx.shared::cta.b64 _, [%0], %1;" ::"r"(bar), "r"(bytes) : "memory");
}
__device__ __forceinline__ void mbar_wait(uint32_t bar, uint32_t parity) {
    uint32_t ok;
    uint32_t spins = 0;
    do {
        asm volatile("{\n.reg .pred p;\n"
                     "mbarrier.try_wait.parity.shared::cta.b64 p, [%1], %2;\n"
                     "selp.b32 %0, 1, 0, p;\n}\n"
                     : "=r"(ok) : "r"(bar), "r"(parity) : "memory");
        if (++spins > (1u << 26)) __trap();
    } while (!ok);
}
__device__ __forceinline__ uint32_t tid_now() {
    uint32_t t;
    asm volatile("mov.u32 %0, %%tid.x;" : "=r"(t));
    return t;
}
__device__ __forceinline__ bool elect_one() {
    uint32_t pred;
    asm volatile("{\n.reg .pred p;\nelect.sync _|p, 0xffffffff;\nselp.b32 %0, 1, 0, p;\n}\n" : "=r"(pred));
    return pred != 0;
}
__device__ __forceinline__ uint32_t wg_uniform() { return __reduce_or_sync(0xffffffffu, tid_now() >> 7); }
constexpr uint32_t kLink = kSmemBase + kOffBar + 64;
constexpr uint32_t kPhase = 1;
constexpr uint32_t kSolo = 2;
constexpr uint32_t kFirst = 4;
constexpr uint32_t kRound = 8;
constexpr uint32_t kVeryFirst = 1u << 16;
__device__ __forceinline__ int st_out(uint32_t st) { return (st >> 4) & 0xfff; }
__device__ __forceinline__ int st_item(uint32_t st) { return st >> 17; }
__device__ __forceinline__ uint32_t baton_wait(uint32_t st, uint32_t packed) {
    if (packed == 0xffffffffu) __trap();
    if (!(st & kSolo)) asm volatile("bar.sync %0, 256;" ::"r"((tid_now() >> 7) + 8) : "memory");
    uint32_t lnk;
    asm volatile("ld.volatile.shared.u32 %0, [%1];" : "=r"(lnk) : "r"(kLink + 8 * (tid_now() >> 7)) : "memory");
    return lnk;
}
__device__ __forceinline__ uint32_t baton_wait_pub(uint32_t st, uint32_t packed, uint32_t& pub) {
    if (packed == 0xffffffffu) __trap();
    asm volatile("bar.sync %0, %1;" ::"r"((tid_now() >> 7) + 8), "r"(st & kSolo ? 128 : 256) : "memory");
    uint32_t lnk;
    asm volatile("ld.volatile.shared.v2.u32 {%0, %1}, [%2];" : "=r"(lnk), "=r"(pub) : "r"(kLink + 8 * (tid_now() >> 7)) : "memory");
    return lnk;
}
__device__ __forceinline__ void baton_pass(uint32_t lnk, uint32_t& st) {
    const bool other = lnk != (tid_now() >> 7) + 8;
    if (other) asm volatile("bar.arrive %0, 256;" ::"r"(lnk) : "memory");
    st = other ? st & ~kSolo : st | kSolo;
}
__device__ __forceinline__ void set_link(int w, uint32_t v) { asm volatile("st.volatile.shared.u32 [%0], %1;" ::"r"(kLink + 8 * w), "r"(v) : "memory"); }
constexpr uint64_t kPolNormal = 0x1000000000000000ull, kPolFirst = 0x12F0000000000000ull;
__device__ __forceinline__ void tma_load_x(uint32_t dst, const CUtensorMap* tm, uint32_t bar, int item) {
    const int wh = (item >> 6) & 63, ww = item & 63;
    asm volatile("cp.async.bulk.tensor.4d.shared::cluster.global.mbarrier::complete_tx::bytes.L2::cache_hint"
                 " [%0], [%1, {%3, %4, %5, %6}], [%2], %7;"
                 ::"r"(dst), "l"(tm), "r"(bar), "r"(0), "r"(ww * 8), "r"(wh * 8), "r"(0), "l"(item >= kEvictFrom ? kPolFirst : kPolNormal) : "memory");
}
__device__ __forceinline__ void tma_load_x_chunk(uint32_t dst, const CUtensorMap* tm, uint32_t bar, int win, int chunk) {
    const int wh = win >> 6, ww = win & 63;
    asm volatile("cp.async.bulk.tensor.4d.shared::cluster.global.mbarrier::complete_tx::bytes"
                 " [%0], [%1, {%3, %4, %5, %6}], [%2];"
                 ::"r"(dst), "l"(tm), "r"(bar), "r"(0), "r"(ww * 8), "r"(wh * 8), "r"(chunk) : "memory");
}
__device__ __forceinline__ void bulk_load(uint32_t dst, const void* src, uint32_t bytes, uint32_t bar) {
    asm volatile("cp.async.bulk.shared::cluster.global.mbarrier::complete_tx::bytes [%0], [%1], %2, [%3];"
                 ::"r"(dst), "l"(src), "r"(bytes), "r"(bar) : "memory");
}

__device__ __forceinline__ void wg_fence()  { asm volatile("wgmma.fence.sync.aligned;" ::: "memory"); }
__device__ __forceinline__ void wg_commit() { asm volatile("wgmma.commit_group.sync.aligned;" ::: "memory"); }
__device__ __forceinline__ void wg_wait0()  { asm volatile("wgmma.wait_group.sync.aligned 0;" ::: "memory"); }
__device__ __forceinline__ void wg_wait1()  { asm volatile("wgmma.wait_group.sync.aligned 1;" ::: "memory"); }
__device__ __forceinline__ void wg_wait2()  { asm volatile("wgmma.wait_group.sync.aligned 2;" ::: "memory"); }

template <int N> __device__ __forceinline__ void fence_regs(float (&d)[N]) {
#pragma unroll
    for (int i = 0; i < N; i++) asm volatile("" : "+f"(d[i])::"memory");
}
template <int N> __device__ __forceinline__ void fence_regs(uint32_t (&d)[N]) {
#pragma unroll
    for (int i = 0; i < N; i++) asm volatile("" : "+r"(d[i])::"memory");
}

#define ACC8(c, d, i) c(d[i]), c(d[i + 1]), c(d[i + 2]), c(d[i + 3]), c(d[i + 4]), c(d[i + 5]), c(d[i + 6]), c(d[i + 7])
#define ACC32(c, d) ACC8(c, d, 0), ACC8(c, d, 8), ACC8(c, d, 16), ACC8(c, d, 24)
#define ACC96(c, d) ACC32(c, d), ACC8(c, d, 32), ACC8(c, d, 40), ACC8(c, d, 48), ACC8(c, d, 56), \
                    ACC8(c, d, 64), ACC8(c, d, 72), ACC8(c, d, 80), ACC8(c, d, 88)
#define C_IO(x) "+f"(x)
#define C_O(x) "=f"(x)
#define REGS32 "{%0, %1, %2, %3, %4, %5, %6, %7, %8, %9, %10, %11, %12, %13, %14, %15, " \
               "%16, %17, %18, %19, %20, %21, %22, %23, %24, %25, %26, %27, %28, %29, %30, %31}"
#define REGS96 "{%0, %1, %2, %3, %4, %5, %6, %7, %8, %9, %10, %11, %12, %13, %14, %15, " \
               "%16, %17, %18, %19, %20, %21, %22, %23, %24, %25, %26, %27, %28, %29, %30, %31, " \
               "%32, %33, %34, %35, %36, %37, %38, %39, %40, %41, %42, %43, %44, %45, %46, %47, " \
               "%48, %49, %50, %51, %52, %53, %54, %55, %56, %57, %58, %59, %60, %61, %62, %63, " \
               "%64, %65, %66, %67, %68, %69, %70, %71, %72, %73, %74, %75, %76, %77, %78, %79, " \
               "%80, %81, %82, %83, %84, %85, %86, %87, %88, %89, %90, %91, %92, %93, %94, %95}"

#define DESC_HI "0x40000040"
#define MK_DESC(name, lo, off) "add.u32 t, " lo ", " off ";\nmov.b64 " name ", {t, " DESC_HI "};\n"

template <bool First, int OA, int OB> __device__ __forceinline__ void wg192_ss(float (&d)[96], uint32_t la, uint32_t lb) {
    if constexpr (First)
        asm volatile("{\n.reg .pred p;\n.reg .b32 t;\n.reg .b64 da, db;\nsetp.ne.b32 p, 0, 0;\n"
                     MK_DESC("da", "%96", "%98") MK_DESC("db", "%97", "%99")
                     "wgmma.mma_async.sync.aligned.m64n192k16.f32.bf16.bf16 " REGS96 ", da, db, p, 1, 1, 0, 0;\n}\n"
                     : ACC96(C_O, d) : "r"(la), "r"(lb), "n"(OA), "n"(OB));
    else
        asm volatile("{\n.reg .pred p;\n.reg .b32 t;\n.reg .b64 da, db;\nsetp.ne.b32 p, 1, 0;\n"
                     MK_DESC("da", "%96", "%98") MK_DESC("db", "%97", "%99")
                     "wgmma.mma_async.sync.aligned.m64n192k16.f32.bf16.bf16 " REGS96 ", da, db, p, 1, 1, 0, 0;\n}\n"
                     : ACC96(C_IO, d) : "r"(la), "r"(lb), "n"(OA), "n"(OB));
}
template <bool First, int TB, int OB> __device__ __forceinline__ void wg192_rs(float (&d)[96], const uint32_t* a, uint32_t lb) {
    if constexpr (First)
        asm volatile("{\n.reg .pred p;\n.reg .b32 t;\n.reg .b64 db;\nsetp.ne.b32 p, 0, 0;\n"
                     MK_DESC("db", "%100", "%102")
                     "wgmma.mma_async.sync.aligned.m64n192k16.f32.bf16.bf16 " REGS96 ", {%96, %97, %98, %99}, db, p, 1, 1, %101;\n}\n"
                     : ACC96(C_O, d) : "r"(a[0]), "r"(a[1]), "r"(a[2]), "r"(a[3]), "r"(lb), "n"(TB), "n"(OB));
    else
        asm volatile("{\n.reg .pred p;\n.reg .b32 t;\n.reg .b64 db;\nsetp.ne.b32 p, 1, 0;\n"
                     MK_DESC("db", "%100", "%102")
                     "wgmma.mma_async.sync.aligned.m64n192k16.f32.bf16.bf16 " REGS96 ", {%96, %97, %98, %99}, db, p, 1, 1, %101;\n}\n"
                     : ACC96(C_IO, d) : "r"(a[0]), "r"(a[1]), "r"(a[2]), "r"(a[3]), "r"(lb), "n"(TB), "n"(OB));
}
template <bool First, int TB, int OB> __device__ __forceinline__ void wg64_rs(float (&d)[32], const uint32_t* a, uint32_t lb) {
    if constexpr (First)
        asm volatile("{\n.reg .pred p;\n.reg .b32 t;\n.reg .b64 db;\nsetp.ne.b32 p, 0, 0;\n"
                     MK_DESC("db", "%36", "%38")
                     "wgmma.mma_async.sync.aligned.m64n64k16.f32.bf16.bf16 " REGS32 ", {%32, %33, %34, %35}, db, p, 1, 1, %37;\n}\n"
                     : ACC32(C_O, d) : "r"(a[0]), "r"(a[1]), "r"(a[2]), "r"(a[3]), "r"(lb), "n"(TB), "n"(OB));
    else
        asm volatile("{\n.reg .pred p;\n.reg .b32 t;\n.reg .b64 db;\nsetp.ne.b32 p, 1, 0;\n"
                     MK_DESC("db", "%36", "%38")
                     "wgmma.mma_async.sync.aligned.m64n64k16.f32.bf16.bf16 " REGS32 ", {%32, %33, %34, %35}, db, p, 1, 1, %37;\n}\n"
                     : ACC32(C_IO, d) : "r"(a[0]), "r"(a[1]), "r"(a[2]), "r"(a[3]), "r"(lb), "n"(TB), "n"(OB));
}
template <int OB> __device__ __forceinline__ void wg64_rs_reuse(float (&d)[32], const uint32_t* a, uint32_t lb, uint32_t one) {
    asm volatile("{\n.reg .pred p;\n.reg .b32 t;\n.reg .b64 db;\nsetp.ne.b32 p, %38, 1;\n"
                 MK_DESC("db", "%36", "%37")
                 "wgmma.mma_async.sync.aligned.m64n64k16.f32.bf16.bf16 " REGS32 ", {%32, %33, %34, %35}, db, p, 1, 1, 0;\n}\n"
                 : ACC32(C_IO, d) : "r"(a[0]), "r"(a[1]), "r"(a[2]), "r"(a[3]), "r"(lb), "n"(OB), "r"(one));
}
__host__ __device__ constexpr int koff(int kk, int chunk) { return ((kk >> 2) * chunk + (kk & 3) * 32) >> 4; }

__device__ __forceinline__ void stsm4(uint32_t addr, const uint4& v) {
    asm volatile("stmatrix.sync.aligned.m8n8.x4.shared.b16 [%0], {%1, %2, %3, %4};" ::"r"(addr), "r"(v.x), "r"(v.y), "r"(v.z), "r"(v.w) : "memory");
}
__device__ __forceinline__ void bulk_wait_read() {
    asm volatile("cp.async.bulk.wait_group.read 0;" ::: "memory");
}
__device__ __forceinline__ uint32_t stage_addr(uint32_t slot, uint32_t l) { return slot + (l & 7) * 128 + ((((l >> 3) & 3) ^ (l & 7)) << 4); }
__device__ __forceinline__ uint32_t tid_opaque() { return __shfl_sync(0xffffffffu, tid_now(), tid_now() & 31); }
template <int R> __device__ __forceinline__ void stage_round(const uint4 (&h)[12], uint32_t sa) {
#pragma unroll
    for (int i = 0; i < 2; i++) {
        const int r = (2 * R + i) / 3, c = (2 * R + i) % 3;
        stsm4(sa + i * 1024, h[4 * c + r]);
        stsm4((sa ^ 64) + i * 1024, h[4 * c + 2 + r]);
    }
}
__device__ __forceinline__ void stage_fence() {
    asm volatile("fence.proxy.async.shared::cta;" ::: "memory");
    __syncwarp();
}
template <int R> __device__ __forceinline__ void send_round(uint32_t slot, const CUtensorMap* tm, int col, int row) {
    asm volatile("{\n.reg .pred p;\nelect.sync _|p, 0xffffffff;\n"
                 "@p cp.async.bulk.tensor.4d.global.shared::cta.bulk_group [%0, {%2, %3, %4, %5}], [%1];\n"
                 "@p cp.async.bulk.commit_group;\n}\n"
                 ::"l"(tm + (R == 1)), "r"(slot), "r"(0), "r"(col), "r"(row + (R == 2)), "r"((int)(R == 2)) : "memory");
}
template <int R> __device__ __forceinline__ void store_round(const uint4 (&h)[12], uint32_t slot, const CUtensorMap* tm, int col, int row) {
    stage_round<R>(h, stage_addr(slot, tid_now()));
    stage_fence();
    send_round<R>(slot, tm, col, row);
}
__device__ __forceinline__ uint32_t warp4_uniform() { return __reduce_or_sync(0xffffffffu, (tid_now() >> 5) & 3); }
struct OutMaps { CUtensorMap m[2]; };
__host__ __device__ constexpr uint32_t bar_m(int c) { return kSmemBase + kOffBar + 32 + 8 * c; }
__device__ __forceinline__ void m_load(const Scratch* sc, int c, uint32_t par) {
    mbar_expect_tx(bar_m(c), 24576);
    bulk_load(kSmemBase + kOffWm + c * 24576, sc->img[par][0] + c * 1536, 24576, bar_m(c));
}
__device__ __forceinline__ bool m_agree(uint32_t ok) {
    uint32_t all;
    asm volatile("{\n.reg .pred p, q;\nsetp.ne.u32 p, %1, 0;\nbar.red.and.pred q, 7, 256, p;\nselp.b32 %0, 1, 0, q;\n}\n" : "=r"(all) : "r"(ok) : "memory");
    return all != 0;
}
__device__ __forceinline__ void m_check(const Scratch* sc, uint32_t par) {
    for (uint32_t round = 0;; round++) {
        uint32_t m = ~0u;
#pragma unroll 1
        for (int c = 0; c < 3; c++) {
            mbar_wait(bar_m(c), round & 1);
#pragma unroll
            for (int j = 0; j < 6; j++) {
                uint32_t v;
                asm volatile("ld.volatile.shared.b32 %0, [%1];" : "=r"(v)
                             : "r"(kSmemBase + kOffWm + c * 24576 + 4096 * j + (tid_now() & 127) * 32 + (tid_now() & 28)) : "memory");
                m = min(m, v);
            }
        }
        if (m_agree(m)) break;
        if (round > (1u << 20)) __trap();
        if (tid_now() == 128) {
            m_load(sc, 0, par); m_load(sc, 1, par); m_load(sc, 2, par);
        }
    }
}
constexpr uint32_t kBarV = kSmemBase + kOffBar + 56;
__device__ __forceinline__ void v_load(const Scratch* sc, uint32_t par) {
    mbar_expect_tx(kBarV, kWBytes);
#pragma unroll 1
    for (int c = 0; c < 3; c++) bulk_load(kSmemBase + kOffWv + c * 24576, sc->img[par][1] + c * 1536, 24576, kBarV);
}
__device__ __forceinline__ void v_check(const Scratch* sc, uint32_t par) {
    for (uint32_t round = 0;; round++) {
        mbar_wait(kBarV, round & 1);
        uint32_t m = ~0u;
#pragma unroll
        for (int j = 0; j < 18; j++) {
            uint32_t v;
            asm volatile("ld.volatile.shared.b32 %0, [%1];" : "=r"(v)
                         : "r"(kSmemBase + kOffWv + 4096 * j + (tid_now() & 127) * 32 + (tid_now() & 28)) : "memory");
            m = min(m, v);
        }
        uint32_t all;
        asm volatile("{\n.reg .pred p, q;\nsetp.ne.u32 p, %1, 0;\nbar.red.and.pred q, 14, 128, p;\nselp.b32 %0, 1, 0, q;\n}\n" : "=r"(all) : "r"(m) : "memory");
        if (all) break;
        if (round > (1u << 20)) __trap();
        if (tid_now() == 352) v_load(sc, par);
    }
}
__host__ __device__ constexpr uint32_t bar_x(int w, int c) { return kSmemBase + kOffBar + 128 + 32 * w + 8 * c; }
template <int K> struct Gemm1 {
    static __device__ __forceinline__ void run(float (&d)[96], uint32_t lx, uint32_t lw, bool very_first, uint32_t st) {
        if constexpr (K > 0) Gemm1<K - 1>::run(d, lx, lw, very_first, st);
        if constexpr (K == 0 || K == 4 || K == 8) {
            if constexpr (K == 0) {
                if (very_first) mbar_wait(bar_m(0), (st & kRound) != 0);
            } else if (st & kFirst) {
                mbar_wait(bar_x(0, K / 4) + 32 * (tid_now() >> 7), 0);
                if (very_first) mbar_wait(bar_m(K / 4), (st & kRound) != 0);
            }
            wg_fence();
        }
        wg192_ss<K == 0, koff(K, 8192), koff(K, 24576)>(d, lx, lw);
    }
};
constexpr uint32_t kScAddr = kSmemBase + kOffBar + 96;
__device__ __forceinline__ void draw_ticket(uint32_t& ticket) {
    asm volatile("{\n.reg .pred p;\n.reg .b64 a;\nsetp.eq.u32 p, %1, 0;\nld.volatile.shared.u64 a, [%3];\n"
                 "@p atom.relaxed.gpu.global.inc.u32 %0, [a], %2;\n}\n"
                 : "+r"(ticket) : "r"(tid_now() & 127), "n"(kNItems - 1), "r"(kScAddr) : "memory");
}
template <int KK> struct Gemm2 { static __device__ __forceinline__ void run(float (&d)[32], const uint32_t* a, uint32_t lx, uint32_t lnk, uint32_t& st) {
    Gemm2<KK - 1>::run(d, a, lx, lnk, st); wg64_rs<KK == 0, 0, koff(KK, 8192)>(d, a + 4 * KK, lx);
    if constexpr (KK == 9) {
        __syncwarp();
        bulk_wait_read();
        baton_pass(lnk, st);
    } } };
template <> struct Gemm2<-1> { static __device__ __forceinline__ void run(float (&)[32], const uint32_t*, uint32_t, uint32_t, uint32_t&) {} };
template <int KK> struct Gemm3 { static __device__ __forceinline__ void run(float (&d)[96], const uint32_t* a, uint32_t lxt) {
    Gemm3<KK - 1>::run(d, a, lxt); wg192_rs<KK == 0, 1, KK * (2048 >> 4)>(d, a + 4 * KK, lxt); } };
template <> struct Gemm3<-1> { static __device__ __forceinline__ void run(float (&)[96], const uint32_t*, uint32_t) {} };
template <int K0, int KK> struct Gemm4 { static __device__ __forceinline__ void run(float (&d)[96], const uint32_t* a, uint32_t lw) {
    if constexpr (KK > K0) Gemm4<K0, KK - 1>::run(d, a, lw);
    wg192_rs<KK == 0, 0, koff(KK, 24576)>(d, a + 4 * KK, lw); } };

template <int C, int KK> struct Gemm3s { static __device__ __forceinline__ void run(float (&d)[32], const uint32_t* a, uint32_t lxt) {
    if constexpr (KK > 0) Gemm3s<C, KK - 1>::run(d, a, lxt);
    wg64_rs<KK == 0, 1, (C * 8192 + KK * 2048) / 16>(d, a + 4 * KK, lxt); } };
template <int C, int K0, int KK> struct Gemm4s { static __device__ __forceinline__ void run(float (&d)[32], const uint32_t* a, uint32_t lw, uint32_t one) {
    if constexpr (KK > K0) Gemm4s<C, K0, KK - 1>::run(d, a, lw, one);
    if constexpr (KK == 0) wg64_rs_reuse<C * 8192 / 16>(d, a, lw, one);
    else wg64_rs<false, 0, koff(KK, 24576) + C * 8192 / 16>(d, a + 4 * KK, lw); } };

__device__ __forceinline__ uint32_t pack_bf16(float lo, float hi) {
    uint32_t r;
    asm("cvt.rn.bf16x2.f32 %0, %1, %2;" : "=r"(r) : "f"(hi), "f"(lo));
    return r;
}
__device__ __forceinline__ float ex2(float x) {
    float r;
    asm("ex2.approx.ftz.f32 %0, %1;" : "=f"(r) : "f"(x));
    return r;
}
__device__ __forceinline__ float rcp(float x) {
    float r;
    asm("rcp.approx.ftz.f32 %0, %1;" : "=f"(r) : "f"(x));
    return r;
}
__device__ __forceinline__ void mma16816(float (&c)[4], uint32_t a0, uint32_t a1, uint32_t a2, uint32_t a3,
                                         uint32_t b0, uint32_t b1) {
    asm volatile("mma.sync.aligned.m16n8k16.row.col.f32.bf16.bf16.f32 {%0,%1,%2,%3}, {%4,%5,%6,%7}, {%8,%9}, {%0,%1,%2,%3};"
                 : "+f"(c[0]), "+f"(c[1]), "+f"(c[2]), "+f"(c[3])
                 : "r"(a0), "r"(a1), "r"(a2), "r"(a3), "r"(b0), "r"(b1));
}

struct FoldRegs { uint4 B0[6], B1[6]; uint32_t A[48]; };

__device__ __forceinline__ void st_relaxed64(void* p, uint32_t a, uint32_t b, uint32_t on) {
    asm volatile("{\n.reg .pred q;\nsetp.ne.u32 q, %3, 0;\n@q st.relaxed.gpu.global.v2.b32 [%0], {%1, %2};\n}\n" ::"l"(p), "r"(a), "r"(b), "r"(on) : "memory");
}
__device__ __forceinline__ uint32_t pack_nonzero(float lo, float hi) { const uint32_t v = pack_bf16(lo, hi); return v != 0 ? v : 0x80000000u; }
__device__ __forceinline__ void fold_store(char* img, uint32_t* cnt, uint32_t epoch, uint32_t on, int n_lo, int n_hi, int k0, int lane, const float (&c0)[4], const float (&c1)[4]) {
    const int q = lane & 3;
    const int u = ((k0 & 63) >> 3) + (q >> 1);
    const int base = (k0 >> 6) * 24576 + (q & 1) * 8;
    char* p_lo = img + (base + n_lo * 128 + ((u ^ (n_lo & 7)) << 4));
    char* p_hi = img + (base + n_hi * 128 + ((u ^ (n_hi & 7)) << 4));
    const uint32_t v0 = pack_nonzero(c0[0], c0[1]);
    const uint32_t par = (epoch & 1) | (v0 & (gridDim.y - 1));
    st_relaxed64(p_lo + par * (2 * kWBytes), v0, pack_nonzero(c1[0], c1[1]), on);
    st_relaxed64(p_hi + par * (2 * kWBytes), pack_nonzero(c0[2], c0[3]), pack_nonzero(c1[2], c1[3]), on);
    asm volatile("{\n.reg .pred q;\nsetp.ne.u32 q, %1, 0;\n@q red.relaxed.gpu.global.inc.u32 [%0], 0xffffffff;\n}\n" ::"l"(cnt), "r"(lane == 0 ? on : 0u) : "memory");
    st_relaxed64(p_lo + (par ^ 1) * (2 * kWBytes), 0, 0, on);
    st_relaxed64(p_hi + (par ^ 1) * (2 * kWBytes), 0, 0, on);
}
__device__ __forceinline__ void fold_load_qk(FoldRegs& r, const __nv_bfloat16* __restrict__ wqkv, int tile, int lane) {
    const int g = lane >> 2, q = lane & 3;
    const int n0 = (tile / 12) * 16, k0 = (tile % 12) * 16;
    const int kb = k0 + 4 * (g >> 1) + (g & 1);
    const uint4* pa0 = reinterpret_cast<const uint4*>(wqkv + (size_t)(n0 + g) * 576 + 192 + 8 * q);
    const uint4* pa1 = reinterpret_cast<const uint4*>(wqkv + (size_t)(n0 + g + 8) * 576 + 192 + 8 * q);
    const uint4* pb0 = reinterpret_cast<const uint4*>(wqkv + (size_t)kb * 576 + 8 * q);
    const uint4* pb1 = reinterpret_cast<const uint4*>(wqkv + (size_t)(kb + 2) * 576 + 8 * q);
#pragma unroll
    for (int j = 0; j < 6; j++) {
        const uint4 lo = __ldg(pa0 + 4 * j), hi = __ldg(pa1 + 4 * j);
        r.A[8 * j + 0] = lo.x; r.A[8 * j + 1] = hi.x; r.A[8 * j + 2] = lo.y; r.A[8 * j + 3] = hi.y;
        r.A[8 * j + 4] = lo.z; r.A[8 * j + 5] = hi.z; r.A[8 * j + 6] = lo.w; r.A[8 * j + 7] = hi.w;
        r.B0[j] = __ldg(pb0 + 4 * j);
        r.B1[j] = __ldg(pb1 + 4 * j);
    }
}
__device__ __forceinline__ void fold_load_vo(FoldRegs& r, const __nv_bfloat16* __restrict__ wqkv, const __nv_bfloat16* __restrict__ wo,
                                             int tile, int lane) {
    const int g = lane >> 2, q = lane & 3;
    const int ch0 = (tile / 12) * 16 + 2 * g;
    const int k0 = (tile % 12) * 16;
    const int kb = k0 + 4 * (g >> 1) + (g & 1);
    const uint4* pb0 = reinterpret_cast<const uint4*>(wqkv + (size_t)kb * 576 + 384 + 8 * q);
    const uint4* pb1 = reinterpret_cast<const uint4*>(wqkv + (size_t)(kb + 2) * 576 + 384 + 8 * q);
    const uint32_t* pw = reinterpret_cast<const uint32_t*>(wo + (size_t)(8 * q) * kC + ch0);
#pragma unroll
    for (int j = 0; j < 6; j++) {
        r.B0[j] = __ldg(pb0 + 4 * j);
        r.B1[j] = __ldg(pb1 + 4 * j);
#pragma unroll
        for (int i = 0; i < 8; i++) r.A[8 * j + i] = __ldg(pw + (32 * j + i) * (kC / 2));
    }
}
template <bool kVO>
__device__ __forceinline__ void fold_compute_store(FoldRegs& r, Scratch* sc, int tile, int lane, uint32_t epoch, uint32_t on) {
    const int g = lane >> 2;
    float c0[4] = {0.f, 0.f, 0.f, 0.f}, c1[4] = {0.f, 0.f, 0.f, 0.f}, c2[4] = {0.f, 0.f, 0.f, 0.f}, c3[4] = {0.f, 0.f, 0.f, 0.f};
#pragma unroll
    for (int j = 0; j < 6; j++) {
        uint32_t a[8];
        if constexpr (kVO) {
#pragma unroll
            for (int i = 0; i < 4; i++) {
                a[2 * i]     = __byte_perm(r.A[8 * j + 2 * i], r.A[8 * j + 2 * i + 1], 0x5410);
                a[2 * i + 1] = __byte_perm(r.A[8 * j + 2 * i], r.A[8 * j + 2 * i + 1], 0x7632);
            }
        } else {
#pragma unroll
            for (int i = 0; i < 8; i++) asm volatile("prmt.b32 %0, %1, 0, 0x3210;" : "=r"(a[i]) : "r"(r.A[8 * j + i]));
        }
        mma16816(c0, a[0], a[1], a[2], a[3], r.B0[j].x, r.B0[j].y);
        mma16816(c1, a[0], a[1], a[2], a[3], r.B1[j].x, r.B1[j].y);
        mma16816(c2, a[4], a[5], a[6], a[7], r.B0[j].z, r.B0[j].w);
        mma16816(c3, a[4], a[5], a[6], a[7], r.B1[j].z, r.B1[j].w);
    }
#pragma unroll
    for (int i = 0; i < 4; i++) { c0[i] += c2[i]; c1[i] += c3[i]; }
    const int k0 = (tile % 12) * 16;
    if constexpr (kVO) {
        const int n = (tile / 12) * 16 + 2 * g;
        fold_store(reinterpret_cast<char*>(sc->img[0][1]), sc->cnt_v, epoch, on, n, n + 1, k0, lane, c0, c1);
    } else {
        const int n0 = (tile / 12) * 16;
        fold_store(reinterpret_cast<char*>(sc->img[0][0]), sc->cnt_m, epoch, on, n0 + g, n0 + g + 8, k0, lane, c0, c1);
    }
}

__device__ __forceinline__ void prefetch_x(const CUtensorMap* tm, int win) {
    const int wh = win >> 6, ww = win & 63;
    asm volatile("cp.async.bulk.prefetch.tensor.3d.L2.global.tile [%0, {%1, %2, %3}];"
                 ::"l"(tm), "r"(0), "r"(ww * 8), "r"(wh * 8) : "memory");
}

__device__ __forceinline__ void reset_for_next_launch() {
    Scratch* q;
    asm volatile("ld.volatile.shared.u64 %0, [%1];" : "=l"(q) : "r"(kScAddr) : "memory");
    q->cnt_v[0] = 0; q->cnt_m[0] = 0; atomicAdd(q->epoch, 1);
}
template <bool Slice> __device__ __forceinline__ void finish_alone(uint32_t dXt, uint32_t dWv, int item) {
    uint32_t pa[16];
#pragma unroll
    for (int j = 0; j < 4; j++)
        asm volatile("ld.volatile.shared.v4.b32 {%0, %1, %2, %3}, [%4];" : "=r"(pa[4 * j]), "=r"(pa[4 * j + 1]), "=r"(pa[4 * j + 2]), "=r"(pa[4 * j + 3])
                     : "r"(kSmemBase + kOffStage + j * 2048 + (tid_now() & 127) * 16) : "memory");
    const uint32_t one = gridDim.y;
    float u0[32], u1[32], u2[32];
    float (&o0)[32] = u0, (&o1)[32] = u2, (&o2)[32] = u0;
    uint32_t fa[48];
    uint4 h[4];
    const float nz = __uint_as_float(one << 31);
    auto pack_a = [&](float (&u)[32], int c) {
        fence_regs(u);
#pragma unroll
        for (int i = 0; i < 16; i++) {
            fa[16 * c + i] = pack_bf16(c != 1 ? u[2 * i] + nz : u[2 * i], u[2 * i + 1]);
            asm volatile("" : "+r"(fa[16 * c + i])::"memory");
        }
        wg_fence();
    };
    auto pack_o = [&](float (&o)[32], bool first) {
        fence_regs(o);
        auto pk = [&](int i) { return pack_bf16(o[i], first ? o[i + 1] + nz : o[i + 1]); };
#pragma unroll
        for (int i = 0; i < 4; i++) {
            const int b = 16 * (i & 1) + 2 * (i >> 1);
            h[i] = make_uint4(pk(b), pk(b + 4), pk(b + 8), pk(b + 12));
        }
#pragma unroll
        for (int i = 0; i < 4; i++) asm volatile("" : "+r"(h[i].x), "+r"(h[i].y), "+r"(h[i].z), "+r"(h[i].w)::"memory");
    };
    wg_fence();
    Gemm3s<0, 3>::run(u0, pa, dXt); wg_commit();
    Gemm3s<1, 3>::run(u1, pa, dXt); wg_commit();
    Gemm3s<2, 3>::run(u2, pa, dXt); wg_commit();
    const uint32_t t = tid_now(), slot = kSmemBase + kOffStage + (t & 96) * 64;
    const uint32_t sa = stage_addr(slot, t);
    const uint32_t tok = (t >> 3) & 3, j = t & 7, la = slot + tok * 128 + ((j ^ tok) << 4);
    char* out;
    asm volatile("ld.volatile.shared.u64 %0, [%1];" : "=l"(out) : "r"(kScAddr + 8) : "memory");
    out += ((((item >> 6) & 63) * 8 + ((t >> 4) & 6)) * kHW + (item & 63) * 8 + tok) * (kC * 2) + j * 16 + (Slice ? ((item >> 12) - 1) * 128 : 0);
    uint4 v[4];
    auto S = [&](int i) { stsm4((sa ^ (i & 1) * 64) + (i >> 1) * 1024, h[i]); };
    auto L = [&](int i) {
        asm volatile("ld.volatile.shared.v4.b32 {%0, %1, %2, %3}, [%4];" : "=r"(v[i].x), "=r"(v[i].y), "=r"(v[i].z), "=r"(v[i].w)
                     : "r"((la ^ (i & 1) * 64) + i * 512) : "memory");
    };
    auto G = [&](int c, int i) {
        asm volatile("st.global.v4.b32 [%0], {%1, %2, %3, %4};"
                     ::"l"(out + ((i >> 1) * kHW + 4 * (i & 1)) * (kC * 2) + c * 128), "r"(v[i].x), "r"(v[i].y), "r"(v[i].z), "r"(v[i].w) : "memory");
    };
#define W(C, K0, K1, O) Gemm4s<C, K0, K1>::run(O, fa, dWv, one)
#define PIN __syncwarp()
    wg_wait2(); pack_a(u0, 0);
    asm volatile("bar.sync %0, 128;" ::"r"((tid_now() >> 7) + 1) : "memory");
    W(0, 0, 3, o0); wg_commit();
    wg_wait2(); pack_a(u1, 1);
    W(0, 4, 7, o0); wg_commit();
    wg_wait2(); pack_a(u2, 2);
    W(0, 8, 11, o0); wg_commit();
    if constexpr (Slice) {
        wg_wait0(); pack_o(o0, true);
        fence_regs(fa);
        S(0); S(1); S(2); S(3); PIN; L(0); L(1); L(2); L(3); G(0, 0); G(0, 1); G(0, 2); G(0, 3);
        return;
    }
    W(1, 0, 5, o1); wg_commit();
    wg_wait1(); pack_o(o0, true);
    W(1, 6, 6, o1); S(0); W(1, 7, 7, o1); S(1); W(1, 8, 8, o1); S(2); W(1, 9, 9, o1); S(3); W(1, 10, 10, o1); PIN; L(0); W(1, 11, 11, o1); wg_commit(); L(1);
    wg_fence();
    W(2, 0, 0, o2); L(2); W(2, 1, 1, o2); L(3); W(2, 2, 2, o2); PIN; G(0, 0); PIN; W(2, 3, 3, o2); G(0, 1); PIN; W(2, 4, 4, o2); G(0, 2); PIN; W(2, 5, 5, o2); wg_commit(); G(0, 3);
    PIN;
    wg_wait1(); pack_o(o1, false);
    W(2, 6, 6, o2); S(0); W(2, 7, 7, o2); S(1); W(2, 8, 8, o2); S(2); W(2, 9, 9, o2); S(3); W(2, 10, 11, o2); wg_commit();
    wg_wait1();
    PIN; L(0); L(1); L(2); L(3); G(1, 0); G(1, 1); G(1, 2); G(1, 3);
    PIN;
    wg_wait0(); pack_o(o2, false);
    fence_regs(fa);
    S(0); S(1); S(2); S(3); PIN; L(0); L(1); L(2); L(3); G(2, 0); G(2, 1); G(2, 2); G(2, 3);
#undef W
#undef PIN
}

__global__ void __launch_bounds__(kThreads, 1)
swin_attn_kernel(const __nv_bfloat16* __restrict__ wqkv, const __nv_bfloat16* __restrict__ wo, Scratch* __restrict__ sc, void* out,
                 const __grid_constant__ OutMaps tmo, const __grid_constant__ CUtensorMap tmx, const __grid_constant__ CUtensorMap tmp, const __grid_constant__ CUtensorMap tmc) {
    extern __shared__ uint8_t smem_raw[];
    constexpr uint32_t sbase = kSmemBase;
    if (smem_u32(smem_raw) != kSmemBase) __trap();
    const int tid = threadIdx.x, lane = tid & 31;
    const uint32_t warpu = __reduce_or_sync(0xffffffffu, (uint32_t)tid >> 5), wgu = warpu >> 2;
    const int warp = (int)warpu, wg = (int)wgu;
    const int G = gridDim.x;

    const int ftile = blockIdx.x + (warp & 1) * G;
    FoldRegs fq;
#pragma unroll
    for (int j = 0; j < 6; j++) {
        asm volatile("" : "=r"(fq.B0[j].x), "=r"(fq.B0[j].y), "=r"(fq.B0[j].z), "=r"(fq.B0[j].w));
        asm volatile("" : "=r"(fq.B1[j].x), "=r"(fq.B1[j].y), "=r"(fq.B1[j].z), "=r"(fq.B1[j].w));
    }
#pragma unroll
    for (int j = 0; j < 48; j++) asm volatile("" : "=r"(fq.A[j]));
    uint32_t epoch;
    asm volatile("ld.relaxed.gpu.global.u32 %0, [%1];" : "=r"(epoch) : "l"(sc->epoch) : "memory");
    if (warp < 2 && ftile < kTiles) fold_load_qk(fq, wqkv, ftile, lane);
    if (warp == 3) {
        const uint32_t i = blockIdx.x + G * (lane & 15);
        const char* p = lane < 16 ? (const char*)wo + i * 128 : (const char*)wqkv + i * 128 + (i / 3 + 1) * 768;
        if (i < 576) asm volatile("prefetch.global.L2 [%0];" ::"l"(p) : "memory");
    }
    if (warp == 10) {
        if (lane == 0) {
#pragma unroll
            for (int w = 0; w < kNWG; w++) {
                mbar_init(sbase + kOffBar + 8 * w, 1);
#pragma unroll
                for (int c = 0; c < 3; c++) mbar_init(bar_x(w, c), 1);
            }
            asm volatile("fence.mbarrier_init.release.cluster;" ::: "memory");
        }
        __syncwarp();
        asm volatile("bar.arrive 11, 384;" ::: "memory");
        if (lane == 0) {
            const uint32_t t0 = (uint32_t)clock64() + kPaceStart + ((blockIdx.x * 37) & 63) * kPaceSpread / 64;
#pragma unroll 1
            for (int i = 0; i <= 3 * kNWG; i++) {
                while ((int)((uint32_t)clock64() - t0) < (i < 3 ? i * kPaceStep0 : kPaceMid + (i - 3) * kPaceStep)) {}
                const int w = i / 3, c = i % 3;
                if (w < kNWG) {
                    mbar_expect_tx(bar_x(w, c), 8192);
                    tma_load_x_chunk(sbase + kOffX + w * kXBytes + c * 8192, &tmc, bar_x(w, c), w * G + blockIdx.x, c);
                } else {
                    prefetch_x(&tmp, kNWG * G + blockIdx.x);
                }
            }
        }
    }
    if (warp < 3) {
        for (int t = ftile;;) {
            const bool on = warp < 2 && t < kTiles;
            fold_compute_store<false>(fq, sc, t, lane, epoch, on);
            t += 2 * G;
            if (__builtin_expect(warp == 2 || t >= kTiles, 1)) break;
            fold_load_qk(fq, wqkv, t, lane);
        }
    }
    if (warp < 4) {
        asm volatile("bar.sync 11, 384;" ::: "memory");
    } else if (warp == 4) {
        if (lane == 0) {
            set_link(0, 9); set_link(1, 8); set_link(2, 8);
            asm volatile("st.shared.v2.u64 [%0], {%1, %2};" ::"r"(kScAddr), "l"(sc), "l"(out) : "memory");
            mbar_init(bar_m(0), 1);
            mbar_init(bar_m(1), 1);
            mbar_init(bar_m(2), 1);
            asm volatile("fence.mbarrier_init.release.cluster;" ::: "memory");
        }
        __syncwarp();
        asm volatile("bar.arrive 12, 128;" ::: "memory");
        uint32_t v;
        asm volatile("ld.relaxed.gpu.global.u32 %0, [%1];" : "=r"(v) : "l"(sc->cnt_m) : "memory");
        asm volatile("bar.sync 11, 384;" ::: "memory");
        { const uint32_t t0 = (uint32_t)clock64(); while ((uint32_t)clock64() - t0 < kPollDelay) {} }
        if (lane == 0) {
            uint32_t spins = 0;
            while (v < kMqkHint) {
                asm volatile("ld.relaxed.gpu.global.u32 %0, [%1];" : "=r"(v) : "l"(sc->cnt_m) : "memory");
                if (++spins > (1u << 22)) __trap();
            }
            const uint32_t par = epoch & 1;
            m_load(sc, 0, par); m_load(sc, 1, par); m_load(sc, 2, par);
        }
    } else if (warp == 11) {
        if (lane == 0) {
            mbar_init(kBarV, 1);
            asm volatile("fence.mbarrier_init.release.cluster;" ::: "memory");
        }
        __syncwarp();
        asm volatile("bar.sync 11, 384;" ::: "memory");
        if (lane == 0) {
            uint32_t v, spins = 0;
            do {
                asm volatile("ld.relaxed.gpu.global.u32 %0, [%1];" : "=r"(v) : "l"(sc->cnt_v) : "memory");
                if (++spins > (1u << 22)) __trap();
            } while (v < kTiles);
            uint32_t ok = 0, n = 0;
            while (!ok && ++n < 64)
                asm volatile("{\n.reg .pred p;\nmbarrier.try_wait.parity.shared::cta.b64 p, [%1], 0;\nselp.b32 %0, 1, 0, p;\n}\n" : "=r"(ok) : "r"(bar_m(2)) : "memory");
            v_load(sc, epoch & 1);
        }
    } else if (warp == 10) {
    } else if (warp >= 8) {
        asm volatile("bar.arrive 11, 384;" ::: "memory");
        if (warp == 9) { const uint32_t t0 = (uint32_t)clock64(); while ((uint32_t)clock64() - t0 < kWvoDelay) {} }
        FoldRegs fr;
        for (int t = G - 1 - blockIdx.x + (warp & 1) * G; t < kTiles; t += 2 * G) {
            fold_load_vo(fr, wqkv, wo, t, lane);
            fold_compute_store<true>(fr, sc, t, lane, epoch, 1);
        }
    } else {
        asm volatile("bar.arrive 11, 384;" ::: "memory");
        if (lane == 0) asm volatile("prefetch.tensormap [%0];" ::"l"(warp == 5 ? &tmo.m[0] : warp == 6 ? &tmo.m[1] : &tmx) : "memory");
        asm volatile("bar.sync 12, 128;" ::: "memory");
    }
    __syncwarp();
    if (wg == 1) m_check(sc, epoch & 1);
    uint4 hv[12];
#pragma unroll
    for (int a = 0; a < 12; a++) asm volatile("" : "=r"(hv[a].x), "=r"(hv[a].y), "=r"(hv[a].z), "=r"(hv[a].w));

    constexpr uint32_t dWm = ((sbase + kOffWm) >> 4) | (1u << 16);
    constexpr uint32_t dWv = ((sbase + kOffWv) >> 4) | (1u << 16);
    const float cs = 0.07216878364870322f * 1.4426950408889634f;
    if (wg == 2) {
        asm volatile("bar.sync 13, 128;" ::: "memory");
        v_check(sc, epoch & 1);
    }
    mbar_wait(bar_x(wg, 0), 0);

    uint32_t st = (uint32_t)(wg * G + blockIdx.x) << 17 | kFirst | kPhase | (wg == 0 ? kSolo | kVeryFirst : 0);

    while (true) {
        float acc[96];
        uint32_t fa[48];
        const uint32_t dX = ((sbase + kOffX + wg_uniform() * kXBytes) >> 4) | (1u << 16);
        uint32_t ticket = 0;
        uint32_t lnk = baton_wait(st, 0);
        while (true) {
            const bool very_first = st & kVeryFirst;
            Gemm1<11>::run(acc, dX, dWm, very_first, st);
            wg_commit();
            if (!very_first) { baton_pass(lnk, st); break; }
            wg_wait0();
            if (m_agree(1)) break;
            st ^= kRound;
        }
        draw_ticket(ticket);
        if (!(st & kFirst)) {
            const uint32_t w4 = warp4_uniform();
            const uint32_t slot = sbase + kOffStage + w4 * 2048;
            const int col = (st_out(st) & 63) * 8, row = (st_out(st) >> 6) * 8 + 2 * w4;
            store_round<0>(hv, slot, tmo.m, col, row);
            bulk_wait_read();
            __syncwarp();
            store_round<1>(hv, slot, tmo.m, col, row);
            bulk_wait_read();
            __syncwarp();
            store_round<2>(hv, slot, tmo.m, col, row);
        }
        static_assert(kPfInit == 2, "one start-up prefetch in the prologue, one here");
        if ((st & kFirst) && tid_now() == 128) prefetch_x(&tmp, (kNWG + (tid_now() >> 7)) * gridDim.x + blockIdx.x);
        __syncwarp();
        wg_wait0();
        fence_regs(acc);
#pragma unroll
        for (int i = 0; i < 48; i++) fa[i] = pack_bf16(acc[2 * i], acc[2 * i + 1]);

        float s[32];
        fence_regs(fa);
        lnk = baton_wait(st, fa[47]);
        wg_fence();
        Gemm2<11>::run(s, fa, dX, lnk, st);
        wg_commit();
        wg_wait0();
        fence_regs(s);
        fence_regs(fa);

        uint32_t pa[16];
        {
            float a0[8], a1[8];
#pragma unroll
            for (int j = 0; j < 8; j++) { a0[j] = fmaxf(s[4 * j], s[4 * j + 1]); a1[j] = fmaxf(s[4 * j + 2], s[4 * j + 3]); }
#pragma unroll
            for (int d = 4; d > 0; d >>= 1)
#pragma unroll
                for (int j = 0; j < d; j++) { a0[j] = fmaxf(a0[j], a0[j + d]); a1[j] = fmaxf(a1[j], a1[j + d]); }
            float m0 = a0[0], m1 = a1[0];
            m0 = fmaxf(m0, __shfl_xor_sync(0xffffffffu, m0, 1));
            m1 = fmaxf(m1, __shfl_xor_sync(0xffffffffu, m1, 1));
            m0 = fmaxf(m0, __shfl_xor_sync(0xffffffffu, m0, 2));
            m1 = fmaxf(m1, __shfl_xor_sync(0xffffffffu, m1, 2));
            m0 *= cs; m1 *= cs;
            float l0 = 0.f, l1 = 0.f;
#pragma unroll
            for (int j = 0; j < 8; j++) {
                s[4 * j]     = ex2(fmaf(s[4 * j], cs, -m0));
                s[4 * j + 1] = ex2(fmaf(s[4 * j + 1], cs, -m0));
                s[4 * j + 2] = ex2(fmaf(s[4 * j + 2], cs, -m1));
                s[4 * j + 3] = ex2(fmaf(s[4 * j + 3], cs, -m1));
                l0 += s[4 * j] + s[4 * j + 1];
                l1 += s[4 * j + 2] + s[4 * j + 3];
            }
            l0 += __shfl_xor_sync(0xffffffffu, l0, 1);
            l1 += __shfl_xor_sync(0xffffffffu, l1, 1);
            l0 += __shfl_xor_sync(0xffffffffu, l0, 2);
            l1 += __shfl_xor_sync(0xffffffffu, l1, 2);
            const float r0 = rcp(l0), r1 = rcp(l1);
#pragma unroll
            for (int j = 0; j < 8; j++) {
                pa[2 * j]     = pack_bf16(s[4 * j] * r0, s[4 * j + 1] * r0);
                pa[2 * j + 1] = pack_bf16(s[4 * j + 2] * r1, s[4 * j + 3] * r1);
            }
        }

        fence_regs(pa);
        if ((tid_now() & 127) == 0) {
            uint32_t item = kNWG * gridDim.x + ticket;
            const uint32_t j = item - (kNWin - kSplit);
            if ((int)j >= 0) {
                const uint32_t q = (j * 21846) >> 16;
                item = j < 3 * kSplit ? (kNWin - kSplit + q) | (j - 3 * q + 1) << 12 : kEnd + (ticket == kNItems - 1);
            }
            asm volatile("st.volatile.shared.u32 [%0], %1;" ::"r"(kLink + 4 + 8 * (tid_now() >> 7)), "r"(item) : "memory");
        }
        uint32_t pub;
        lnk = baton_wait_pub(st, pa[15], pub);
        if ((st & kFirst) && tid_now() == 0) set_link(1, 10);
        const bool alone = lnk == (tid_now() >> 7) + 8 && pub >= kEnd;
        asm volatile("{\n.reg .pred p;\nsetp.ne.u32 p, %16, 0;\n"
                     "@p st.volatile.shared.v4.b32 [%17], {%0, %1, %2, %3};\n@p st.volatile.shared.v4.b32 [%17 + 2048], {%4, %5, %6, %7};\n"
                     "@p st.volatile.shared.v4.b32 [%17 + 4096], {%8, %9, %10, %11};\n@p st.volatile.shared.v4.b32 [%17 + 6144], {%12, %13, %14, %15};\n}\n"
                     :: "r"(pa[0]), "r"(pa[1]), "r"(pa[2]), "r"(pa[3]), "r"(pa[4]), "r"(pa[5]), "r"(pa[6]), "r"(pa[7]),
                        "r"(pa[8]), "r"(pa[9]), "r"(pa[10]), "r"(pa[11]), "r"(pa[12]), "r"(pa[13]), "r"(pa[14]), "r"(pa[15]),
                        "r"((uint32_t)alone), "r"(sbase + kOffStage + (tid_now() & 127) * 16) : "memory");
        if (alone) {
            if (pub == kEnd + 1 && (tid_now() & 127) == 0) reset_for_next_launch();
            __syncwarp();
            const uint32_t slice = __reduce_or_sync(0xffffffffu, st >> 29);
            if (slice) finish_alone<true>(dX + (((8192u >> 4) - 1) << 16), dWv + (slice - 1) * (8192 / 16), st_item(st));
            else finish_alone<false>(dX + (((8192u >> 4) - 1) << 16), dWv, st_item(st));
            return;
        }
        wg_fence();
        Gemm3<3>::run(acc, pa, dX + (((8192u >> 4) - 1) << 16));
        wg_commit();
        baton_pass(lnk, st);
        const int nxt = (int)__reduce_or_sync(0xffffffffu, pub);
        wg_wait0();
        fence_regs(acc);
        fence_regs(pa);

        if (((tid_now() >> 5) & 3) == 0 && nxt < kEnd) {
            asm volatile("bar.sync %0, 128;" ::"r"((tid_now() >> 7) + 1) : "memory");
            if (elect_one()) {
                const uint32_t wgl = tid_now() >> 7;
                const uint32_t bar = sbase + kOffBar + 8 * wgl;
                mbar_expect_tx(bar, kXBytes);
                tma_load_x(sbase + kOffX + wgl * kXBytes, &tmx, bar, nxt);
            }
            __syncwarp();
        } else {
            asm volatile("bar.arrive %0, 128;" ::"r"((tid_now() >> 7) + 1) : "memory");
        }
#pragma unroll
        for (int i = 0; i < 48; i++) fa[i] = pack_bf16(acc[2 * i], acc[2 * i + 1]);

        asm volatile("st.volatile.shared.v4.b32 [%4], {%0, %1, %2, %3};"
                     :: "r"(fa[44]), "r"(fa[45]), "r"(fa[46]), "r"(fa[47]), "r"(sbase + kOffStash + (tid_now() & 127) * 16) : "memory");
        fence_regs(fa);
        if (((tid_now() >> 5) & 3) == 0 && nxt + kPfMin < kNWin) {
            if (elect_one()) {
                const int base = kNWG * (int)gridDim.x, t = nxt - base;
                const int hi = min(nxt + pf_lead(t), kNWin - 1);
                int lo = max(max(nxt - 1 + pf_lead(t - 1), nxt) + 1, base + kPfInit * (int)gridDim.x);
#pragma unroll 1
                for (; lo <= hi; lo++) prefetch_x(&tmp, lo);
            }
            __syncwarp();
        }
        lnk = baton_wait(st, fa[43]);
        if (nxt >= kEnd) {
            if ((tid_now() & 127) == 0) {
#pragma unroll
                for (int w = 0; w < kNWG; w++) {
                    uint32_t l;
                    asm volatile("ld.volatile.shared.u32 %0, [%1];" : "=r"(l) : "r"(kLink + 8 * w) : "memory");
                    if (l == (tid_now() >> 7) + 8) set_link(w, lnk);
                }
            }
        }
        __syncwarp();
        wg_fence();
        Gemm4<0, 1>::run(acc, fa, dWv);
        wg_commit();
        Gemm4<2, 10>::run(acc, fa, dWv);
        wg_commit();
        wg_wait1();
        uint32_t fl[4];
        asm volatile("ld.volatile.shared.v4.b32 {%0, %1, %2, %3}, [%4];"
                     : "=r"(fl[0]), "=r"(fl[1]), "=r"(fl[2]), "=r"(fl[3]) : "r"(sbase + kOffStash + (tid_now() & 127) * 16) : "memory");
        wg_fence();
        wg192_rs<false, 0, koff(11, 24576)>(acc, fl, dWv);
        wg_commit();
        baton_pass(lnk, st);
        if (nxt == kEnd + 1 && (tid_now() & 127) == 0) reset_for_next_launch();
        __syncwarp();
        st = ((st ^ kPhase) & (kPhase | kSolo)) | (st_item(st) & 0xfff) << 4 | nxt << 17;
        uint32_t landed = 1;
        if (nxt < kEnd)
            asm volatile("{\n.reg .pred p;\nmbarrier.test_wait.parity.shared::cta.b64 p, [%1], %2;\nselp.b32 %0, 1, 0, p;\n}\n"
                         : "=r"(landed) : "r"(sbase + kOffBar + 8 * (tid_now() >> 7)), "r"(st & kPhase) : "memory");
        wg_wait0();
        fence_regs(acc);
        fence_regs(fa);
        fence_regs(fl);

#pragma unroll
        for (int a = 0; a < 6; a++)
#pragma unroll
            for (int r = 0; r < 2; r++)
                hv[2 * a + r] = make_uint4(pack_bf16(acc[16 * a + 2 * r], acc[16 * a + 2 * r + 1]), pack_bf16(acc[16 * a + 2 * r + 4], acc[16 * a + 2 * r + 5]),
                                           pack_bf16(acc[16 * a + 2 * r + 8], acc[16 * a + 2 * r + 9]), pack_bf16(acc[16 * a + 2 * r + 12], acc[16 * a + 2 * r + 13]));
        if (nxt >= kEnd) break;
        if (!landed) mbar_wait(sbase + kOffBar + 8 * (tid_now() >> 7), st & kPhase);
    }
    asm volatile("bar.sync %0, 128;" ::"r"((tid_now() >> 7) + 1) : "memory");
    {
        const uint32_t t = tid_opaque(), wu = __reduce_or_sync(0xffffffffu, t >> 5), w4 = wu & 3;
        const uint32_t slot = sbase + kOffX + wu * 6144, sa = stage_addr(slot, t);
        const int col = (st_out(st) & 63) * 8, row = (st_out(st) >> 6) * 8 + 2 * w4;
        stage_round<0>(hv, sa);
        stage_round<1>(hv, sa + 2048);
        stage_round<2>(hv, sa + 4096);
        stage_fence();
        send_round<0>(slot, tmo.m, col, row);
        send_round<1>(slot + 2048, tmo.m, col, row);
        send_round<2>(slot + 4096, tmo.m, col, row);
    }
    bulk_wait_read();
}

typedef CUresult (*EncodeTiledFn)(CUtensorMap*, CUtensorMapDataType, cuuint32_t, void*, const cuuint64_t*,
                                  const cuuint64_t*, const cuuint32_t*, const cuuint32_t*, CUtensorMapInterleave,
                                  CUtensorMapSwizzle, CUtensorMapL2promotion, CUtensorMapFloatOOBfill);

}

extern "C" void kernel_launch(void* const* d_in, const int* in_sizes, int n_in, void* d_out, int out_size) {
    (void)in_sizes; (void)n_in; (void)out_size;
    const __nv_bfloat16* x    = (const __nv_bfloat16*)d_in[0];
    const __nv_bfloat16* wqkv = (const __nv_bfloat16*)d_in[1];
    const __nv_bfloat16* wo   = (const __nv_bfloat16*)d_in[2];

    static EncodeTiledFn encode = nullptr;
    static int num_sms = 0;
    static Scratch* scratch = nullptr;
    if (!encode) {
        void* fn = nullptr;
        cudaDriverEntryPointQueryResult qr;
        cudaGetDriverEntryPoint("cuTensorMapEncodeTiled", &fn, cudaEnableDefault, &qr);
        encode = (EncodeTiledFn)fn;
        cudaGetSymbolAddress((void**)&scratch, g_scratch);
        int dev = 0;
        cudaGetDevice(&dev);
        cudaDeviceGetAttribute(&num_sms, cudaDevAttrMultiProcessorCount, dev);
        cudaFuncSetAttribute(swin_attn_kernel, cudaFuncAttributeMaxDynamicSharedMemorySize, kSmemBytes);
    }
    CUtensorMap tmx;
    const cuuint64_t gdim[4] = {64, (cuuint64_t)kHW, (cuuint64_t)kHW, 3};
    const cuuint64_t gstr[3] = {(cuuint64_t)kC * 2, (cuuint64_t)kHW * kC * 2, 128};
    const cuuint32_t box[4] = {64, 8, 8, 3};
    const cuuint32_t estr[4] = {1, 1, 1, 1};
    encode(&tmx, CU_TENSOR_MAP_DATA_TYPE_BFLOAT16, 4, (void*)x, gdim, gstr, box, estr, CU_TENSOR_MAP_INTERLEAVE_NONE,
           CU_TENSOR_MAP_SWIZZLE_128B, CU_TENSOR_MAP_L2_PROMOTION_NONE, CU_TENSOR_MAP_FLOAT_OOB_FILL_NONE);

    CUtensorMap tmp;
    const cuuint64_t pdim[3] = {(cuuint64_t)kC, (cuuint64_t)kHW, (cuuint64_t)kHW};
    const cuuint64_t pstr[2] = {(cuuint64_t)kC * 2, (cuuint64_t)kHW * kC * 2};
    const cuuint32_t pbox[3] = {(cuuint32_t)kC, 8, 8};
    encode(&tmp, CU_TENSOR_MAP_DATA_TYPE_BFLOAT16, 3, (void*)x, pdim, pstr, pbox, estr, CU_TENSOR_MAP_INTERLEAVE_NONE,
           CU_TENSOR_MAP_SWIZZLE_NONE, CU_TENSOR_MAP_L2_PROMOTION_NONE, CU_TENSOR_MAP_FLOAT_OOB_FILL_NONE);
    CUtensorMap tmc;
    const cuuint32_t boxc[4] = {64, 8, 8, 1};
    encode(&tmc, CU_TENSOR_MAP_DATA_TYPE_BFLOAT16, 4, (void*)x, gdim, gstr, boxc, estr, CU_TENSOR_MAP_INTERLEAVE_NONE,
           CU_TENSOR_MAP_SWIZZLE_128B, CU_TENSOR_MAP_L2_PROMOTION_NONE, CU_TENSOR_MAP_FLOAT_OOB_FILL_NONE);
    OutMaps tmo;
    const cuuint32_t boxo[4] = {64, 8, 1, 2};
    encode(&tmo.m[0], CU_TENSOR_MAP_DATA_TYPE_BFLOAT16, 4, d_out, gdim, gstr, boxo, estr, CU_TENSOR_MAP_INTERLEAVE_NONE,
           CU_TENSOR_MAP_SWIZZLE_128B, CU_TENSOR_MAP_L2_PROMOTION_NONE, CU_TENSOR_MAP_FLOAT_OOB_FILL_NONE);
    const cuuint64_t odim[4] = {64, (cuuint64_t)kHW, (cuuint64_t)kHW, 2};
    const cuuint64_t ostr[3] = {(cuuint64_t)kC * 2, (cuuint64_t)kHW * kC * 2, (cuuint64_t)kHW * kC * 2 - 256};
    encode(&tmo.m[1], CU_TENSOR_MAP_DATA_TYPE_BFLOAT16, 4, (char*)d_out + 256, odim, ostr, boxo, estr, CU_TENSOR_MAP_INTERLEAVE_NONE,
           CU_TENSOR_MAP_SWIZZLE_128B, CU_TENSOR_MAP_L2_PROMOTION_NONE, CU_TENSOR_MAP_FLOAT_OOB_FILL_NONE);
    swin_attn_kernel<<<num_sms, kThreads, kSmemBytes, cudaStreamPerThread>>>(wqkv, wo, scratch, d_out, tmo, tmx, tmp, tmc);
}
```

```cpp
#include <cuda_runtime.h>
#include <cuda_bf16.h>
#include <cuda.h>
#include <stdint.h>

namespace {

constexpr int kC      = 192;
constexpr int kHW     = 512;
constexpr int kNWin   = 4096;
constexpr int kXBytes = 64 * kC * 2;
constexpr int kWBytes = kC * kC * 2;
constexpr int kNWG    = 3;
constexpr int kThreads = kNWG * 128;
constexpr int kTiles  = 144;
constexpr int kPfInit = 2, kPfUp = 160, kPfPeak = 400, kPfHold = 800, kPfDown1 = 40, kPfBase2 = 300, kPfDown2 = 12, kPfMin = 140;
__device__ __forceinline__ int pf_lead(int t) {
    return min(min(kPfInit * (int)gridDim.x + ((t * kPfUp) >> 8), kPfPeak),
               max(max(kPfPeak - (((t - kPfHold) * kPfDown1) >> 8), kPfBase2 - ((t * kPfDown2) >> 8)), kPfMin));
}
constexpr int kEvictFrom = 3100;
constexpr int kPaceStart = 100, kPaceSpread = 500, kPaceStep0 = 750, kPaceMid = 2100, kPaceStep = 550;
constexpr uint32_t kMqkHint = 72;
constexpr uint32_t kPollDelay = 200;
constexpr uint32_t kWvoDelay = 1000;

constexpr int kOffWm  = 0;
constexpr int kOffWv  = kWBytes;
constexpr int kOffX   = 2 * kWBytes;
constexpr int kOffStage = kOffX + kNWG * kXBytes;
constexpr int kOffStash = kOffStage + 8192;
constexpr int kOffBar = kOffStash + 2048;
constexpr int kSmemBytes = kOffBar + 256;
constexpr uint32_t kSmemBase = 1024;

struct Scratch {
    uint32_t ticket[32];
    uint32_t epoch[32];
    uint32_t cnt_v[32];
    uint32_t cnt_m[32];
    uint4 img[2][2][kWBytes / 16];
};
__device__ __align__(128) Scratch g_scratch;

__device__ __forceinline__ uint32_t smem_u32(const void* p) { return (uint32_t)__cvta_generic_to_shared(p); }

__device__ __forceinline__ void mbar_init(uint32_t bar, uint32_t count) {
    asm volatile("mbarrier.init.shared::cta.b64 [%0], %1;" ::"r"(bar), "r"(count) : "memory");
}
__device__ __forceinline__ void mbar_expect_tx(uint32_t bar, uint32_t bytes) {
    asm volatile("mbarrier.arrive.expect_tx.shared::cta.b64 _, [%0], %1;" ::"r"(bar), "r"(bytes) : "memory");
}
__device__ __forceinline__ void mbar_wait(uint32_t bar, uint32_t parity) {
    uint32_t ok;
    uint32_t spins = 0;
    do {
        asm volatile("{\n.reg .pred p;\n"
                     "mbarrier.try_wait.parity.shared::cta.b64 p, [%1], %2;\n"
                     "selp.b32 %0, 1, 0, p;\n}\n"
                     : "=r"(ok) : "r"(bar), "r"(parity) : "memory");
        if (++spins > (1u << 26)) __trap();
    } while (!ok);
}
__device__ __forceinline__ uint32_t tid_now() {
    uint32_t t;
    asm volatile("mov.u32 %0, %%tid.x;" : "=r"(t));
    return t;
}
__device__ __forceinline__ bool elect_one() {
    uint32_t pred;
    asm volatile("{\n.reg .pred p;\nelect.sync _|p, 0xffffffff;\nselp.b32 %0, 1, 0, p;\n}\n" : "=r"(pred));
    return pred != 0;
}
__device__ __forceinline__ uint32_t wg_uniform() { return __reduce_or_sync(0xffffffffu, tid_now() >> 7); }
constexpr uint32_t kLink = kSmemBase + kOffBar + 64;
constexpr uint32_t kMarks = kLink + 24;
constexpr uint32_t kPhase = 1;
constexpr uint32_t kSolo = 2;
constexpr uint32_t kFirst = 4;
constexpr uint32_t kRound = 8;
constexpr uint32_t kVeryFirst = 1u << 16;
__device__ __forceinline__ int st_out(uint32_t st) { return (st >> 4) & 0xfff; }
__device__ __forceinline__ int st_win(uint32_t st) { return st >> 17; }
__device__ __forceinline__ uint32_t baton_wait(uint32_t st, uint32_t packed) {
    if (packed == 0xffffffffu) __trap();
    if (!(st & kSolo)) asm volatile("bar.sync %0, 256;" ::"r"((tid_now() >> 7) + 8) : "memory");
    uint32_t lnk;
    asm volatile("ld.volatile.shared.u32 %0, [%1];" : "=r"(lnk) : "r"(kLink + 8 * (tid_now() >> 7)) : "memory");
    return lnk;
}
__device__ __forceinline__ uint32_t baton_wait_pub(uint32_t st, uint32_t packed, uint32_t& pub) {
    if (packed == 0xffffffffu) __trap();
    asm volatile("bar.sync %0, %1;" ::"r"((tid_now() >> 7) + 8), "r"(st & kSolo ? 128 : 256) : "memory");
    uint32_t lnk;
    asm volatile("ld.volatile.shared.v2.u32 {%0, %1}, [%2];" : "=r"(lnk), "=r"(pub) : "r"(kLink + 8 * (tid_now() >> 7)) : "memory");
    return lnk;
}
__device__ __forceinline__ void baton_pass(uint32_t lnk, uint32_t& st) {
    const bool other = lnk != (tid_now() >> 7) + 8;
    if (other) asm volatile("bar.arrive %0, 256;" ::"r"(lnk) : "memory");
    st = other ? st & ~kSolo : st | kSolo;
}
__device__ __forceinline__ void set_link(int w, uint32_t v) { asm volatile("st.volatile.shared.u32 [%0], %1;" ::"r"(kLink + 8 * w), "r"(v) : "memory"); }
constexpr uint64_t kPolNormal = 0x1000000000000000ull, kPolFirst = 0x12F0000000000000ull;
__device__ __forceinline__ void tma_load_x(uint32_t dst, const CUtensorMap* tm, uint32_t bar, int win) {
    const int wh = win >> 6, ww = win & 63;
    asm volatile("cp.async.bulk.tensor.4d.shared::cluster.global.mbarrier::complete_tx::bytes.L2::cache_hint"
                 " [%0], [%1, {%3, %4, %5, %6}], [%2], %7;"
                 ::"r"(dst), "l"(tm), "r"(bar), "r"(0), "r"(ww * 8), "r"(wh * 8), "r"(0), "l"(win >= kEvictFrom ? kPolFirst : kPolNormal) : "memory");
}
__device__ __forceinline__ void tma_load_x_chunk(uint32_t dst, const CUtensorMap* tm, uint32_t bar, int win, int chunk) {
    const int wh = win >> 6, ww = win & 63;
    asm volatile("cp.async.bulk.tensor.4d.shared::cluster.global.mbarrier::complete_tx::bytes"
                 " [%0], [%1, {%3, %4, %5, %6}], [%2];"
                 ::"r"(dst), "l"(tm), "r"(bar), "r"(0), "r"(ww * 8), "r"(wh * 8), "r"(chunk) : "memory");
}
__device__ __forceinline__ void bulk_load(uint32_t dst, const void* src, uint32_t bytes, uint32_t bar) {
    asm volatile("cp.async.bulk.shared::cluster.global.mbarrier::complete_tx::bytes [%0], [%1], %2, [%3];"
                 ::"r"(dst), "l"(src), "r"(bytes), "r"(bar) : "memory");
}

__device__ __forceinline__ void wg_fence()  { asm volatile("wgmma.fence.sync.aligned;" ::: "memory"); }
__device__ __forceinline__ void wg_commit() { asm volatile("wgmma.commit_group.sync.aligned;" ::: "memory"); }
__device__ __forceinline__ void wg_wait0()  { asm volatile("wgmma.wait_group.sync.aligned 0;" ::: "memory"); }
__device__ __forceinline__ void wg_wait1()  { asm volatile("wgmma.wait_group.sync.aligned 1;" ::: "memory"); }
__device__ __forceinline__ void wg_wait2()  { asm volatile("wgmma.wait_group.sync.aligned 2;" ::: "memory"); }

template <int N> __device__ __forceinline__ void fence_regs(float (&d)[N]) {
#pragma unroll
    for (int i = 0; i < N; i++) asm volatile("" : "+f"(d[i])::"memory");
}
template <int N> __device__ __forceinline__ void fence_regs(uint32_t (&d)[N]) {
#pragma unroll
    for (int i = 0; i < N; i++) asm volatile("" : "+r"(d[i])::"memory");
}

#define ACC8(c, d, i) c(d[i]), c(d[i + 1]), c(d[i + 2]), c(d[i + 3]), c(d[i + 4]), c(d[i + 5]), c(d[i + 6]), c(d[i + 7])
#define ACC32(c, d) ACC8(c, d, 0), ACC8(c, d, 8), ACC8(c, d, 16), ACC8(c, d, 24)
#define ACC96(c, d) ACC32(c, d), ACC8(c, d, 32), ACC8(c, d, 40), ACC8(c, d, 48), ACC8(c, d, 56), \
                    ACC8(c, d, 64), ACC8(c, d, 72), ACC8(c, d, 80), ACC8(c, d, 88)
#define C_IO(x) "+f"(x)
#define C_O(x) "=f"(x)
#define REGS32 "{%0, %1, %2, %3, %4, %5, %6, %7, %8, %9, %10, %11, %12, %13, %14, %15, " \
               "%16, %17, %18, %19, %20, %21, %22, %23, %24, %25, %26, %27, %28, %29, %30, %31}"
#define REGS96 "{%0, %1, %2, %3, %4, %5, %6, %7, %8, %9, %10, %11, %12, %13, %14, %15, " \
               "%16, %17, %18, %19, %20, %21, %22, %23, %24, %25, %26, %27, %28, %29, %30, %31, " \
               "%32, %33, %34, %35, %36, %37, %38, %39, %40, %41, %42, %43, %44, %45, %46, %47, " \
               "%48, %49, %50, %51, %52, %53, %54, %55, %56, %57, %58, %59, %60, %61, %62, %63, " \
               "%64, %65, %66, %67, %68, %69, %70, %71, %72, %73, %74, %75, %76, %77, %78, %79, " \
               "%80, %81, %82, %83, %84, %85, %86, %87, %88, %89, %90, %91, %92, %93, %94, %95}"

#define DESC_HI "0x40000040"
#define MK_DESC(name, lo, off) "add.u32 t, " lo ", " off ";\nmov.b64 " name ", {t, " DESC_HI "};\n"

template <bool First, int OA, int OB> __device__ __forceinline__ void wg192_ss(float (&d)[96], uint32_t la, uint32_t lb) {
    if constexpr (First)
        asm volatile("{\n.reg .pred p;\n.reg .b32 t;\n.reg .b64 da, db;\nsetp.ne.b32 p, 0, 0;\n"
                     MK_DESC("da", "%96", "%98") MK_DESC("db", "%97", "%99")
                     "wgmma.mma_async.sync.aligned.m64n192k16.f32.bf16.bf16 " REGS96 ", da, db, p, 1, 1, 0, 0;\n}\n"
                     : ACC96(C_O, d) : "r"(la), "r"(lb), "n"(OA), "n"(OB));
    else
        asm volatile("{\n.reg .pred p;\n.reg .b32 t;\n.reg .b64 da, db;\nsetp.ne.b32 p, 1, 0;\n"
                     MK_DESC("da", "%96", "%98") MK_DESC("db", "%97", "%99")
                     "wgmma.mma_async.sync.aligned.m64n192k16.f32.bf16.bf16 " REGS96 ", da, db, p, 1, 1, 0, 0;\n}\n"
                     : ACC96(C_IO, d) : "r"(la), "r"(lb), "n"(OA), "n"(OB));
}
template <bool First, int TB, int OB> __device__ __forceinline__ void wg192_rs(float (&d)[96], const uint32_t* a, uint32_t lb) {
    if constexpr (First)
        asm volatile("{\n.reg .pred p;\n.reg .b32 t;\n.reg .b64 db;\nsetp.ne.b32 p, 0, 0;\n"
                     MK_DESC("db", "%100", "%102")
                     "wgmma.mma_async.sync.aligned.m64n192k16.f32.bf16.bf16 " REGS96 ", {%96, %97, %98, %99}, db, p, 1, 1, %101;\n}\n"
                     : ACC96(C_O, d) : "r"(a[0]), "r"(a[1]), "r"(a[2]), "r"(a[3]), "r"(lb), "n"(TB), "n"(OB));
    else
        asm volatile("{\n.reg .pred p;\n.reg .b32 t;\n.reg .b64 db;\nsetp.ne.b32 p, 1, 0;\n"
                     MK_DESC("db", "%100", "%102")
                     "wgmma.mma_async.sync.aligned.m64n192k16.f32.bf16.bf16 " REGS96 ", {%96, %97, %98, %99}, db, p, 1, 1, %101;\n}\n"
                     : ACC96(C_IO, d) : "r"(a[0]), "r"(a[1]), "r"(a[2]), "r"(a[3]), "r"(lb), "n"(TB), "n"(OB));
}
template <bool First, int TB, int OB> __device__ __forceinline__ void wg64_rs(float (&d)[32], const uint32_t* a, uint32_t lb) {
    if constexpr (First)
        asm volatile("{\n.reg .pred p;\n.reg .b32 t;\n.reg .b64 db;\nsetp.ne.b32 p, 0, 0;\n"
                     MK_DESC("db", "%36", "%38")
                     "wgmma.mma_async.sync.aligned.m64n64k16.f32.bf16.bf16 " REGS32 ", {%32, %33, %34, %35}, db, p, 1, 1, %37;\n}\n"
                     : ACC32(C_O, d) : "r"(a[0]), "r"(a[1]), "r"(a[2]), "r"(a[3]), "r"(lb), "n"(TB), "n"(OB));
    else
        asm volatile("{\n.reg .pred p;\n.reg .b32 t;\n.reg .b64 db;\nsetp.ne.b32 p, 1, 0;\n"
                     MK_DESC("db", "%36", "%38")
                     "wgmma.mma_async.sync.aligned.m64n64k16.f32.bf16.bf16 " REGS32 ", {%32, %33, %34, %35}, db, p, 1, 1, %37;\n}\n"
                     : ACC32(C_IO, d) : "r"(a[0]), "r"(a[1]), "r"(a[2]), "r"(a[3]), "r"(lb), "n"(TB), "n"(OB));
}
template <int OB> __device__ __forceinline__ void wg64_rs_reuse(float (&d)[32], const uint32_t* a, uint32_t lb, uint32_t one) {
    asm volatile("{\n.reg .pred p;\n.reg .b32 t;\n.reg .b64 db;\nsetp.ne.b32 p, %38, 1;\n"
                 MK_DESC("db", "%36", "%37")
                 "wgmma.mma_async.sync.aligned.m64n64k16.f32.bf16.bf16 " REGS32 ", {%32, %33, %34, %35}, db, p, 1, 1, 0;\n}\n"
                 : ACC32(C_IO, d) : "r"(a[0]), "r"(a[1]), "r"(a[2]), "r"(a[3]), "r"(lb), "n"(OB), "r"(one));
}
__host__ __device__ constexpr int koff(int kk, int chunk) { return ((kk >> 2) * chunk + (kk & 3) * 32) >> 4; }

__device__ __forceinline__ void stsm4(uint32_t addr, const uint4& v) {
    asm volatile("stmatrix.sync.aligned.m8n8.x4.shared.b16 [%0], {%1, %2, %3, %4};" ::"r"(addr), "r"(v.x), "r"(v.y), "r"(v.z), "r"(v.w) : "memory");
}
__device__ __forceinline__ void bulk_wait_read() {
    asm volatile("cp.async.bulk.wait_group.read 0;" ::: "memory");
}
__device__ __forceinline__ uint32_t stage_addr(uint32_t slot, uint32_t l) { return slot + (l & 7) * 128 + ((((l >> 3) & 3) ^ (l & 7)) << 4); }
__device__ __forceinline__ void stage_fence() {
    asm volatile("fence.proxy.async.shared::cta;" ::: "memory");
    __syncwarp();
}
template <int R> __device__ __forceinline__ void store_round(const uint4 (&h)[12], uint32_t slot, const CUtensorMap* tm, int col, int row) {
    const uint32_t sa = stage_addr(slot, tid_now());
#pragma unroll
    for (int i = 0; i < 2; i++) {
        const int r = (2 * R + i) / 3, c = (2 * R + i) % 3;
        stsm4(sa + i * 1024, h[4 * c + r]);
        stsm4((sa ^ 64) + i * 1024, h[4 * c + 2 + r]);
    }
    stage_fence();
    asm volatile("{\n.reg .pred p;\nelect.sync _|p, 0xffffffff;\n"
                 "@p cp.async.bulk.tensor.4d.global.shared::cta.bulk_group [%0, {%2, %3, %4, %5}], [%1];\n"
                 "@p cp.async.bulk.commit_group;\n}\n"
                 ::"l"(tm + (R == 1)), "r"(slot), "r"(0), "r"(col), "r"(row + (R == 2)), "r"((int)(R == 2)) : "memory");
}
__device__ __forceinline__ uint32_t warp4_uniform() { return __reduce_or_sync(0xffffffffu, (tid_now() >> 5) & 3); }
struct OutMaps { CUtensorMap m[3]; };
__host__ __device__ constexpr uint32_t bar_m(int c) { return kSmemBase + kOffBar + 32 + 8 * c; }
__device__ __forceinline__ void m_load(const Scratch* sc, int c, uint32_t par) {
    mbar_expect_tx(bar_m(c), 24576);
    bulk_load(kSmemBase + kOffWm + c * 24576, sc->img[par][0] + c * 1536, 24576, bar_m(c));
}
__device__ __forceinline__ bool m_agree(uint32_t ok) {
    uint32_t all;
    asm volatile("{\n.reg .pred p, q;\nsetp.ne.u32 p, %1, 0;\nbar.red.and.pred q, 7, 256, p;\nselp.b32 %0, 1, 0, q;\n}\n" : "=r"(all) : "r"(ok) : "memory");
    return all != 0;
}
__device__ __forceinline__ void m_check(const Scratch* sc, uint32_t par) {
    for (uint32_t round = 0;; round++) {
        uint32_t m = ~0u;
#pragma unroll 1
        for (int c = 0; c < 3; c++) {
            mbar_wait(bar_m(c), round & 1);
#pragma unroll
            for (int j = 0; j < 6; j++) {
                uint32_t v;
                asm volatile("ld.volatile.shared.b32 %0, [%1];" : "=r"(v)
                             : "r"(kSmemBase + kOffWm + c * 24576 + 4096 * j + (tid_now() & 127) * 32 + (tid_now() & 28)) : "memory");
                m = min(m, v);
            }
        }
        if (m_agree(m)) break;
        asm volatile("bar.sync 7, 256;" ::: "memory");
        if (round > (1u << 20)) __trap();
        if (tid_now() == 128) {
            m_load(sc, 0, par); m_load(sc, 1, par); m_load(sc, 2, par);
        }
    }
}
constexpr uint32_t kBarV = kSmemBase + kOffBar + 56;
__device__ __forceinline__ void v_load(const Scratch* sc, uint32_t par) {
    mbar_expect_tx(kBarV, kWBytes);
#pragma unroll 1
    for (int c = 0; c < 3; c++) bulk_load(kSmemBase + kOffWv + c * 24576, sc->img[par][1] + c * 1536, 24576, kBarV);
}
__device__ __forceinline__ void v_check(const Scratch* sc, uint32_t par) {
    for (uint32_t round = 0;; round++) {
        mbar_wait(kBarV, round & 1);
        uint32_t m = ~0u;
#pragma unroll
        for (int j = 0; j < 18; j++) {
            uint32_t v;
            asm volatile("ld.volatile.shared.b32 %0, [%1];" : "=r"(v)
                         : "r"(kSmemBase + kOffWv + 4096 * j + (tid_now() & 127) * 32 + (tid_now() & 28)) : "memory");
            m = min(m, v);
        }
        uint32_t all;
        asm volatile("{\n.reg .pred p, q;\nsetp.ne.u32 p, %1, 0;\nbar.red.and.pred q, 14, 128, p;\nselp.b32 %0, 1, 0, q;\n}\n" : "=r"(all) : "r"(m) : "memory");
        if (all) break;
        if (round > (1u << 20)) __trap();
        if (tid_now() == 352) v_load(sc, par);
    }
}
__host__ __device__ constexpr uint32_t bar_x(int w, int c) { return kSmemBase + kOffBar + 128 + 32 * w + 8 * c; }
template <int K> struct Gemm1 {
    static __device__ __forceinline__ void run(float (&d)[96], uint32_t lx, uint32_t lw, bool very_first, uint32_t st) {
        if constexpr (K > 0) Gemm1<K - 1>::run(d, lx, lw, very_first, st);
        if constexpr (K == 0 || K == 4 || K == 8) {
            if constexpr (K == 0) {
                if (very_first) mbar_wait(bar_m(0), (st & kRound) != 0);
            } else if (st & kFirst) {
                mbar_wait(bar_x(0, K / 4) + 32 * (tid_now() >> 7), 0);
                if (very_first) mbar_wait(bar_m(K / 4), (st & kRound) != 0);
            }
            wg_fence();
        }
        wg192_ss<K == 0, koff(K, 8192), koff(K, 24576)>(d, lx, lw);
    }
};
constexpr uint32_t kScAddr = kSmemBase + kOffBar + 96;
__device__ __forceinline__ void draw_ticket(uint32_t& ticket) {
    asm volatile("{\n.reg .pred p;\n.reg .b64 a;\nsetp.eq.u32 p, %1, 0;\nld.volatile.shared.u64 a, [%3];\n"
                 "@p atom.relaxed.gpu.global.inc.u32 %0, [a], %2;\n}\n"
                 : "+r"(ticket) : "r"(tid_now() & 127), "n"(kNWin - 1), "r"(kScAddr) : "memory");
}
template <int KK> struct Gemm2 { static __device__ __forceinline__ void run(float (&d)[32], const uint32_t* a, uint32_t lx, uint32_t lnk, uint32_t& st) {
    Gemm2<KK - 1>::run(d, a, lx, lnk, st); wg64_rs<KK == 0, 0, koff(KK, 8192)>(d, a + 4 * KK, lx);
    if constexpr (KK == 9) {
        __syncwarp();
        bulk_wait_read();
        baton_pass(lnk, st);
    } } };
template <> struct Gemm2<-1> { static __device__ __forceinline__ void run(float (&)[32], const uint32_t*, uint32_t, uint32_t, uint32_t&) {} };
template <int KK> struct Gemm3 { static __device__ __forceinline__ void run(float (&d)[96], const uint32_t* a, uint32_t lxt) {
    Gemm3<KK - 1>::run(d, a, lxt); wg192_rs<KK == 0, 1, KK * (2048 >> 4)>(d, a + 4 * KK, lxt); } };
template <> struct Gemm3<-1> { static __device__ __forceinline__ void run(float (&)[96], const uint32_t*, uint32_t) {} };
template <int K0, int KK> struct Gemm4 { static __device__ __forceinline__ void run(float (&d)[96], const uint32_t* a, uint32_t lw) {
    if constexpr (KK > K0) Gemm4<K0, KK - 1>::run(d, a, lw);
    wg192_rs<KK == 0, 0, koff(KK, 24576)>(d, a + 4 * KK, lw); } };

template <int C, int KK> struct Gemm3s { static __device__ __forceinline__ void run(float (&d)[32], const uint32_t* a, uint32_t lxt) {
    if constexpr (KK > 0) Gemm3s<C, KK - 1>::run(d, a, lxt);
    wg64_rs<KK == 0, 1, (C * 8192 + KK * 2048) / 16>(d, a + 4 * KK, lxt); } };
template <int C, int K0, int KK> struct Gemm4s { static __device__ __forceinline__ void run(float (&d)[32], const uint32_t* a, uint32_t lw, uint32_t one) {
    if constexpr (KK > K0) Gemm4s<C, K0, KK - 1>::run(d, a, lw, one);
    if constexpr (KK == 0) wg64_rs_reuse<C * 8192 / 16>(d, a, lw, one);
    else wg64_rs<false, 0, koff(KK, 24576) + C * 8192 / 16>(d, a + 4 * KK, lw); } };

__device__ __forceinline__ uint32_t pack_bf16(float lo, float hi) {
    uint32_t r;
    asm("cvt.rn.bf16x2.f32 %0, %1, %2;" : "=r"(r) : "f"(hi), "f"(lo));
    return r;
}
__device__ __forceinline__ float ex2(float x) {
    float r;
    asm("ex2.approx.ftz.f32 %0, %1;" : "=f"(r) : "f"(x));
    return r;
}
__device__ __forceinline__ float rcp(float x) {
    float r;
    asm("rcp.approx.ftz.f32 %0, %1;" : "=f"(r) : "f"(x));
    return r;
}
__device__ __forceinline__ void mma16816(float (&c)[4], uint32_t a0, uint32_t a1, uint32_t a2, uint32_t a3,
                                         uint32_t b0, uint32_t b1) {
    asm volatile("mma.sync.aligned.m16n8k16.row.col.f32.bf16.bf16.f32 {%0,%1,%2,%3}, {%4,%5,%6,%7}, {%8,%9}, {%0,%1,%2,%3};"
                 : "+f"(c[0]), "+f"(c[1]), "+f"(c[2]), "+f"(c[3])
                 : "r"(a0), "r"(a1), "r"(a2), "r"(a3), "r"(b0), "r"(b1));
}

struct FoldRegs { uint4 B0[6], B1[6]; uint32_t A[48]; };

__device__ __forceinline__ void st_relaxed64(void* p, uint32_t a, uint32_t b, uint32_t on) {
    asm volatile("{\n.reg .pred q;\nsetp.ne.u32 q, %3, 0;\n@q st.relaxed.gpu.global.v2.b32 [%0], {%1, %2};\n}\n" ::"l"(p), "r"(a), "r"(b), "r"(on) : "memory");
}
__device__ __forceinline__ uint32_t pack_nonzero(float lo, float hi) { const uint32_t v = pack_bf16(lo, hi); return v != 0 ? v : 0x80000000u; }
__device__ __forceinline__ void fold_store(char* img, uint32_t* cnt, uint32_t epoch, uint32_t on, int n_lo, int n_hi, int k0, int lane, const float (&c0)[4], const float (&c1)[4]) {
    const int q = lane & 3;
    const int u = ((k0 & 63) >> 3) + (q >> 1);
    const int base = (k0 >> 6) * 24576 + (q & 1) * 8;
    char* p_lo = img + (base + n_lo * 128 + ((u ^ (n_lo & 7)) << 4));
    char* p_hi = img + (base + n_hi * 128 + ((u ^ (n_hi & 7)) << 4));
    const uint32_t v0 = pack_nonzero(c0[0], c0[1]);
    const uint32_t par = (epoch & 1) | (v0 & (gridDim.y - 1));
    st_relaxed64(p_lo + par * (2 * kWBytes), v0, pack_nonzero(c1[0], c1[1]), on);
    st_relaxed64(p_hi + par * (2 * kWBytes), pack_nonzero(c0[2], c0[3]), pack_nonzero(c1[2], c1[3]), on);
    asm volatile("{\n.reg .pred q;\nsetp.ne.u32 q, %1, 0;\n@q red.relaxed.gpu.global.inc.u32 [%0], 0xffffffff;\n}\n" ::"l"(cnt), "r"(lane == 0 ? on : 0u) : "memory");
    st_relaxed64(p_lo + (par ^ 1) * (2 * kWBytes), 0, 0, on);
    st_relaxed64(p_hi + (par ^ 1) * (2 * kWBytes), 0, 0, on);
}
__device__ __forceinline__ void fold_load_qk(FoldRegs& r, const __nv_bfloat16* __restrict__ wqkv, int tile, int lane) {
    const int g = lane >> 2, q = lane & 3;
    const int n0 = (tile / 12) * 16, k0 = (tile % 12) * 16;
    const int kb = k0 + 4 * (g >> 1) + (g & 1);
    const uint4* pa0 = reinterpret_cast<const uint4*>(wqkv + (size_t)(n0 + g) * 576 + 192 + 8 * q);
    const uint4* pa1 = reinterpret_cast<const uint4*>(wqkv + (size_t)(n0 + g + 8) * 576 + 192 + 8 * q);
    const uint4* pb0 = reinterpret_cast<const uint4*>(wqkv + (size_t)kb * 576 + 8 * q);
    const uint4* pb1 = reinterpret_cast<const uint4*>(wqkv + (size_t)(kb + 2) * 576 + 8 * q);
#pragma unroll
    for (int j = 0; j < 6; j++) {
        const uint4 lo = __ldg(pa0 + 4 * j), hi = __ldg(pa1 + 4 * j);
        r.A[8 * j + 0] = lo.x; r.A[8 * j + 1] = hi.x; r.A[8 * j + 2] = lo.y; r.A[8 * j + 3] = hi.y;
        r.A[8 * j + 4] = lo.z; r.A[8 * j + 5] = hi.z; r.A[8 * j + 6] = lo.w; r.A[8 * j + 7] = hi.w;
        r.B0[j] = __ldg(pb0 + 4 * j);
        r.B1[j] = __ldg(pb1 + 4 * j);
    }
}
__device__ __forceinline__ void fold_load_vo(FoldRegs& r, const __nv_bfloat16* __restrict__ wqkv, const __nv_bfloat16* __restrict__ wo,
                                             int tile, int lane) {
    const int g = lane >> 2, q = lane & 3;
    const int ch0 = (tile / 12) * 16 + 2 * g;
    const int k0 = (tile % 12) * 16;
    const int kb = k0 + 4 * (g >> 1) + (g & 1);
    const uint4* pb0 = reinterpret_cast<const uint4*>(wqkv + (size_t)kb * 576 + 384 + 8 * q);
    const uint4* pb1 = reinterpret_cast<const uint4*>(wqkv + (size_t)(kb + 2) * 576 + 384 + 8 * q);
    const uint32_t* pw = reinterpret_cast<const uint32_t*>(wo + (size_t)(8 * q) * kC + ch0);
#pragma unroll
    for (int j = 0; j < 6; j++) {
        r.B0[j] = __ldg(pb0 + 4 * j);
        r.B1[j] = __ldg(pb1 + 4 * j);
#pragma unroll
        for (int i = 0; i < 8; i++) r.A[8 * j + i] = __ldg(pw + (32 * j + i) * (kC / 2));
    }
}
template <bool kVO>
__device__ __forceinline__ void fold_compute_store(FoldRegs& r, Scratch* sc, int tile, int lane, uint32_t epoch, uint32_t on) {
    const int g = lane >> 2;
    float c0[4] = {0.f, 0.f, 0.f, 0.f}, c1[4] = {0.f, 0.f, 0.f, 0.f}, c2[4] = {0.f, 0.f, 0.f, 0.f}, c3[4] = {0.f, 0.f, 0.f, 0.f};
#pragma unroll
    for (int j = 0; j < 6; j++) {
        uint32_t a[8];
        if constexpr (kVO) {
#pragma unroll
            for (int i = 0; i < 4; i++) {
                a[2 * i]     = __byte_perm(r.A[8 * j + 2 * i], r.A[8 * j + 2 * i + 1], 0x5410);
                a[2 * i + 1] = __byte_perm(r.A[8 * j + 2 * i], r.A[8 * j + 2 * i + 1], 0x7632);
            }
        } else {
#pragma unroll
            for (int i = 0; i < 8; i++) asm volatile("prmt.b32 %0, %1, 0, 0x3210;" : "=r"(a[i]) : "r"(r.A[8 * j + i]));
        }
        mma16816(c0, a[0], a[1], a[2], a[3], r.B0[j].x, r.B0[j].y);
        mma16816(c1, a[0], a[1], a[2], a[3], r.B1[j].x, r.B1[j].y);
        mma16816(c2, a[4], a[5], a[6], a[7], r.B0[j].z, r.B0[j].w);
        mma16816(c3, a[4], a[5], a[6], a[7], r.B1[j].z, r.B1[j].w);
    }
#pragma unroll
    for (int i = 0; i < 4; i++) { c0[i] += c2[i]; c1[i] += c3[i]; }
    const int k0 = (tile % 12) * 16;
    if constexpr (kVO) {
        const int n = (tile / 12) * 16 + 2 * g;
        fold_store(reinterpret_cast<char*>(sc->img[0][1]), sc->cnt_v, epoch, on, n, n + 1, k0, lane, c0, c1);
    } else {
        const int n0 = (tile / 12) * 16;
        fold_store(reinterpret_cast<char*>(sc->img[0][0]), sc->cnt_m, epoch, on, n0 + g, n0 + g + 8, k0, lane, c0, c1);
    }
}

__device__ __forceinline__ void prefetch_x(const CUtensorMap* tm, int win) {
    const int wh = win >> 6, ww = win & 63;
    asm volatile("cp.async.bulk.prefetch.tensor.3d.L2.global.tile [%0, {%1, %2, %3}];"
                 ::"l"(tm), "r"(0), "r"(ww * 8), "r"(wh * 8) : "memory");
}

__device__ __forceinline__ void publish(uint32_t ticket) {
    if (ticket == kNWin - 1) {
        Scratch* q;
        asm volatile("ld.volatile.shared.u64 %0, [%1];" : "=l"(q) : "r"(kScAddr) : "memory");
        q->cnt_v[0] = 0; q->cnt_m[0] = 0; atomicAdd(q->epoch, 1);
    }
    asm volatile("st.volatile.shared.u32 [%0], %1;" ::"r"(kLink + 4 + 8 * (tid_now() >> 7)), "r"(kNWG * gridDim.x + ticket) : "memory");
}

__device__ __forceinline__ void send_slice(const CUtensorMap* tm, uint32_t slot, uint32_t col, uint32_t row, uint32_t c) {
    stage_fence();
    asm volatile("{\n.reg .pred p;\nelect.sync _|p, 0xffffffff;\n"
                 "@p cp.async.bulk.tensor.4d.global.shared::cta.bulk_group [%0, {%2, %3, %4, %5}], [%1];\n}\n"
                 ::"l"(tm + 2), "r"(slot + c * 2048), "r"(0), "r"(col), "r"(row), "r"(c) : "memory");
}
__device__ __forceinline__ void bulk_commit() { asm volatile("cp.async.bulk.commit_group;" ::: "memory"); }
template <bool AddNz> __device__ __forceinline__ void pack_slice(uint4 (&h)[4], float (&o)[32], float nz) {
    fence_regs(o);
    auto pk = [&](int i) { return pack_bf16(o[i], AddNz ? o[i + 1] + nz : o[i + 1]); };
#pragma unroll
    for (int i = 0; i < 4; i++) {
        const int b = 16 * (i & 1) + 2 * (i >> 1);
        h[i] = make_uint4(pk(b), pk(b + 4), pk(b + 8), pk(b + 12));
    }
#pragma unroll
    for (int i = 0; i < 4; i++) asm volatile("" : "+r"(h[i].x), "+r"(h[i].y), "+r"(h[i].z), "+r"(h[i].w)::"memory");
}
__device__ __forceinline__ void stage_part(uint32_t sa, int c, const uint4 (&h)[4], int i) { stsm4((sa ^ (i & 1) * 64) + (i >> 1) * 1024 + c * 2048, h[i]); }
#define W(C, K0, K1, O) Gemm4s<C, K0, K1>::run(O, fa, dWv, one)
#define W_STAGE(C, O) stage_part(sa, C - 1, h, 0); W(C, 5, 5, O); stage_part(sa, C - 1, h, 1); W(C, 6, 6, O); \
                      stage_part(sa, C - 1, h, 2); W(C, 7, 7, O); stage_part(sa, C - 1, h, 3); W(C, 8, 8, O)

__device__ __forceinline__ void finish_alone(const uint32_t (&pa_in)[16], uint32_t dXt, uint32_t dWv, const CUtensorMap* tm, uint32_t st) {
    uint32_t pa[16];
#pragma unroll
    for (int j = 0; j < 16; j++) pa[j] = pa_in[j];
    char* out;
    asm volatile("ld.volatile.shared.u64 %0, [%1];" : "=l"(out) : "r"(kScAddr + 8) : "memory");
    const uint32_t one = gridDim.y;
    const float nz = __uint_as_float(one << 31);
    float u0[32], u1[32], u2[32];
    float (&o0)[32] = u0, (&o1)[32] = u2, (&o2)[32] = u0;
    uint32_t fa[48];
    uint4 h[4];
    auto pack_a = [&](float (&u)[32], int c) {
        fence_regs(u);
#pragma unroll
        for (int i = 0; i < 16; i++) {
            fa[16 * c + i] = pack_bf16(c != 1 ? u[2 * i] + nz : u[2 * i], u[2 * i + 1]);
            asm volatile("" : "+r"(fa[16 * c + i])::"memory");
        }
        wg_fence();
    };
    const uint32_t t = tid_now(), win = st_win(st);
    const uint32_t slot = kSmemBase + kOffX + (t >> 5) * 6144, sa = stage_addr(slot, t);
    const uint32_t col = (win & 63) * 8, row = (win >> 6) * 8 + ((t >> 4) & 6);
    if (!(st & kSolo)) asm volatile("bar.sync %0, 256;" ::"r"((t >> 7) + 8) : "memory");
    wg_fence();
    Gemm3s<0, 3>::run(u0, pa, dXt); wg_commit();
    Gemm3s<1, 3>::run(u1, pa, dXt); wg_commit();
    Gemm3s<2, 3>::run(u2, pa, dXt); wg_commit();
    wg_wait2(); pack_a(u0, 0);
    W(0, 0, 3, o0); wg_commit();
    wg_wait2(); pack_a(u1, 1);
    W(0, 4, 7, o0); wg_commit();
    wg_wait2(); pack_a(u2, 2);
    W(0, 8, 11, o0); wg_commit();
    W(1, 0, 0, o1);
    asm volatile("bar.sync %0, 128;" ::"r"((t >> 7) + 1) : "memory");
    wg_fence();
    W(1, 1, 4, o1); wg_commit();
    wg_wait1(); pack_slice<true>(h, o0, nz);
    W_STAGE(1, o1);
    W(1, 9, 10, o1);
    send_slice(tm, slot, col, row, 0);
    wg_fence();
    W(1, 11, 11, o1); wg_commit();
    W(2, 0, 4, o2); wg_commit();
    wg_wait1(); pack_slice<false>(h, o1, nz);
    W_STAGE(2, o2);
    W(2, 9, 10, o2);
    send_slice(tm, slot, col, row, 1);
    wg_fence();
    W(2, 11, 11, o2); wg_commit();
    __syncwarp();
    bulk_commit();
    __syncwarp();
    wg_wait0(); pack_slice<false>(h, o2, nz);
    fence_regs(fa);
#pragma unroll
    for (int i = 0; i < 4; i++) stage_part(sa, 2, h, i);
    __syncwarp();
    const uint32_t tok = (t >> 3) & 3, j = t & 7, la = slot + tok * 128 + ((j ^ tok) << 4);
    out += (row * kHW + col + tok) * (kC * 2) + j * 16 + 256;
#pragma unroll
    for (int i = 0; i < 4; i++)
        asm volatile("ld.volatile.shared.v4.b32 {%0, %1, %2, %3}, [%4];" : "=r"(h[i].x), "=r"(h[i].y), "=r"(h[i].z), "=r"(h[i].w)
                     : "r"((la ^ (i & 1) * 64) + i * 512 + 4096) : "memory");
#pragma unroll
    for (int i = 0; i < 4; i++)
        asm volatile("st.global.v4.b32 [%0], {%1, %2, %3, %4};"
                     ::"l"(out + ((i >> 1) * kHW + 4 * (i & 1)) * (kC * 2)), "r"(h[i].x), "r"(h[i].y), "r"(h[i].z), "r"(h[i].w) : "memory");
    __syncwarp();
    bulk_wait_read();
}

__device__ __forceinline__ void finish_last(const uint32_t (&fa_in)[48], uint32_t dWv, const CUtensorMap* tm, uint32_t st) {
    uint32_t fa[48];
#pragma unroll
    for (int j = 0; j < 48; j++) fa[j] = fa_in[j];
    const uint32_t one = gridDim.y;
    const float nz = __uint_as_float(one << 31);
    float o0[32], o1[32];
    float (&o2)[32] = o0;
    uint4 h[4];
    const uint32_t t = tid_now(), win = st_win(st);
    const uint32_t slot = kSmemBase + kOffX + (t >> 5) * 6144, sa = stage_addr(slot, t);
    const uint32_t col = (win & 63) * 8, row = (win >> 6) * 8 + ((t >> 4) & 6);
    const uint32_t la = kLink + 8 * min(t & 127, 2u), me = (t >> 7) + 8;
    uint32_t pub, l;
    const uint32_t lnk = baton_wait_pub(st, sa + la + col + row, pub);
    asm volatile("ld.volatile.shared.u32 %0, [%1];" : "=r"(l) : "r"(la) : "memory");
    wg_fence();
    wg64_rs<true, 0, 0>(o0, fa, dWv);
    W(0, 1, 3, o0);
    asm volatile("{\n.reg .pred p;\nsetp.eq.u32 p, %0, %1;\n@p st.volatile.shared.u32 [%2], %3;\n}\n" ::"r"(l), "r"(me), "r"(la), "r"(lnk) : "memory");
    W(0, 4, 11, o0); wg_commit();
    wg64_rs<true, 0, 8192 / 16>(o1, fa, dWv);
    W(1, 1, 4, o1); wg_commit();
    wg_wait1(); pack_slice<false>(h, o0, nz);
    W_STAGE(1, o1);
    W(1, 9, 10, o1);
    send_slice(tm, slot, col, row, 0);
    wg_fence();
    W(1, 11, 11, o1); wg_commit();
    W(2, 0, 4, o2); wg_commit();
    wg_wait1(); pack_slice<false>(h, o1, nz);
    W_STAGE(2, o2);
    W(2, 9, 9, o2);
    asm volatile("{\n.reg .pred p;\nsetp.ne.u32 p, %0, %1;\n@p bar.arrive %0, 256;\n}\n" ::"r"(lnk), "r"(me) : "memory");
    wg_fence();
    W(2, 10, 11, o2); wg_commit();
    send_slice(tm, slot, col, row, 1);
    wg_wait0(); pack_slice<true>(h, o2, nz);
    fence_regs(fa);
#pragma unroll
    for (int i = 0; i < 4; i++) stage_part(sa, 2, h, i);
    send_slice(tm, slot, col, row, 2);
    bulk_commit();
    bulk_wait_read();
}
#undef W
#undef W_STAGE

__global__ void __launch_bounds__(kThreads, 1)
swin_attn_kernel(const __nv_bfloat16* __restrict__ wqkv, const __nv_bfloat16* __restrict__ wo, Scratch* __restrict__ sc, void* out,
                 const __grid_constant__ OutMaps tmo, const __grid_constant__ CUtensorMap tmx, const __grid_constant__ CUtensorMap tmp, const __grid_constant__ CUtensorMap tmc) {
    extern __shared__ uint8_t smem_raw[];
    constexpr uint32_t sbase = kSmemBase;
    const int tid = threadIdx.x, lane = tid & 31;
    const int G = gridDim.x;

    FoldRegs fq;
#pragma unroll
    for (int j = 0; j < 6; j++) {
        asm volatile("" : "=r"(fq.B0[j].x), "=r"(fq.B0[j].y), "=r"(fq.B0[j].z), "=r"(fq.B0[j].w));
        asm volatile("" : "=r"(fq.B1[j].x), "=r"(fq.B1[j].y), "=r"(fq.B1[j].z), "=r"(fq.B1[j].w));
    }
#pragma unroll
    for (int j = 0; j < 48; j++) asm volatile("" : "=r"(fq.A[j]));
    uint32_t epoch;
    asm volatile("ld.relaxed.gpu.global.u32 %0, [%1];" : "=r"(epoch) : "l"(sc->epoch) : "memory");
    {
        const int t = blockIdx.x + (tid & 32 ? G : 0);
        if (tid < 64 && t < kTiles) fold_load_qk(fq, wqkv, t, lane);
    }
    __syncwarp();
    if (smem_u32(smem_raw) != kSmemBase) __trap();
    const uint32_t warpu = __reduce_or_sync(0xffffffffu, (uint32_t)tid >> 5), wgu = warpu >> 2;
    const int warp = (int)warpu, wg = (int)wgu;
    const int ftile = blockIdx.x + (warp & 1) * G;
    if (warp == 3) {
        const uint32_t i = blockIdx.x + G * (lane & 15);
        const char* p = lane < 16 ? (const char*)wo + i * 128 : (const char*)wqkv + i * 128 + (i / 3 + 1) * 768;
        if (i < 576) asm volatile("prefetch.global.L2 [%0];" ::"l"(p) : "memory");
    }
    if (warp == 10) {
        if (lane == 0) {
#pragma unroll
            for (int w = 0; w < kNWG; w++) {
                mbar_init(sbase + kOffBar + 8 * w, 1);
#pragma unroll
                for (int c = 0; c < 3; c++) mbar_init(bar_x(w, c), 1);
            }
            asm volatile("fence.mbarrier_init.release.cluster;" ::: "memory");
        }
        __syncwarp();
        asm volatile("bar.arrive 11, 384;" ::: "memory");
        if (lane == 0) {
            const uint32_t t0 = (uint32_t)clock64() + kPaceStart + ((blockIdx.x * 37) & 63) * kPaceSpread / 64;
#pragma unroll 1
            for (int i = 0; i <= 3 * kNWG; i++) {
                while ((int)((uint32_t)clock64() - t0) < (i < 3 ? i * kPaceStep0 : kPaceMid + (i - 3) * kPaceStep)) {}
                const int w = i / 3, c = i % 3;
                if (w < kNWG) {
                    mbar_expect_tx(bar_x(w, c), 8192);
                    tma_load_x_chunk(sbase + kOffX + w * kXBytes + c * 8192, &tmc, bar_x(w, c), w * G + blockIdx.x, c);
                } else {
                    prefetch_x(&tmp, kNWG * G + blockIdx.x);
                }
            }
        }
    }
    if (warp < 3) {
        for (int t = ftile;;) {
            const bool on = warp < 2 && t < kTiles;
            fold_compute_store<false>(fq, sc, t, lane, epoch, on);
            t += 2 * G;
            if (__builtin_expect(warp == 2 || t >= kTiles, 1)) break;
            fold_load_qk(fq, wqkv, t, lane);
        }
    }
    if (warp < 4) {
        asm volatile("bar.sync 11, 384;" ::: "memory");
    } else if (warp == 4) {
        if (lane == 0) {
            asm volatile("st.shared.v4.u32 [%0], {9, 0, 8, 0};\nst.shared.v4.u32 [%0 + 16], {8, 0, 0, 0};" ::"r"(kLink) : "memory");
            asm volatile("st.shared.v2.u64 [%0], {%1, %2};" ::"r"(kScAddr), "l"(sc), "l"(out) : "memory");
            mbar_init(bar_m(0), 1);
            mbar_init(bar_m(1), 1);
            mbar_init(bar_m(2), 1);
            asm volatile("fence.mbarrier_init.release.cluster;" ::: "memory");
        }
        __syncwarp();
        asm volatile("bar.arrive 12, 128;" ::: "memory");
        uint32_t v;
        asm volatile("ld.relaxed.gpu.global.u32 %0, [%1];" : "=r"(v) : "l"(sc->cnt_m) : "memory");
        asm volatile("bar.sync 11, 384;" ::: "memory");
        { const uint32_t t0 = (uint32_t)clock64(); while ((uint32_t)clock64() - t0 < kPollDelay) {} }
        if (lane == 0) {
            uint32_t spins = 0;
            while (v < kMqkHint) {
                asm volatile("ld.relaxed.gpu.global.u32 %0, [%1];" : "=r"(v) : "l"(sc->cnt_m) : "memory");
                if (++spins > (1u << 22)) __trap();
            }
            const uint32_t par = epoch & 1;
            m_load(sc, 0, par); m_load(sc, 1, par); m_load(sc, 2, par);
        }
    } else if (warp == 11) {
        if (lane == 0) {
            mbar_init(kBarV, 1);
            asm volatile("fence.mbarrier_init.release.cluster;" ::: "memory");
        }
        __syncwarp();
        asm volatile("bar.sync 11, 384;" ::: "memory");
        if (lane == 0) {
            uint32_t v, spins = 0;
            do {
                asm volatile("ld.relaxed.gpu.global.u32 %0, [%1];" : "=r"(v) : "l"(sc->cnt_v) : "memory");
                if (++spins > (1u << 22)) __trap();
            } while (v < kTiles);
            uint32_t ok = 0, n = 0;
            while (!ok && ++n < 64)
                asm volatile("{\n.reg .pred p;\nmbarrier.try_wait.parity.shared::cta.b64 p, [%1], 0;\nselp.b32 %0, 1, 0, p;\n}\n" : "=r"(ok) : "r"(bar_m(2)) : "memory");
            v_load(sc, epoch & 1);
        }
    } else if (warp == 10) {
    } else if (warp >= 8) {
        asm volatile("bar.arrive 11, 384;" ::: "memory");
        if (warp == 9) { const uint32_t t0 = (uint32_t)clock64(); while ((uint32_t)clock64() - t0 < kWvoDelay) {} }
        FoldRegs fr;
        for (int t = G - 1 - blockIdx.x + (warp & 1) * G; t < kTiles; t += 2 * G) {
            fold_load_vo(fr, wqkv, wo, t, lane);
            fold_compute_store<true>(fr, sc, t, lane, epoch, 1);
        }
    } else {
        asm volatile("bar.arrive 11, 384;" ::: "memory");
        if (lane == 0) asm volatile("prefetch.tensormap [%0];" ::"l"(warp == 5 ? &tmo.m[0] : warp == 6 ? &tmo.m[1] : &tmx) : "memory");
        if (lane == 0 && warp == 5) asm volatile("prefetch.tensormap [%0];" ::"l"(&tmo.m[2]) : "memory");
        asm volatile("bar.sync 12, 128;" ::: "memory");
    }
    __syncwarp();
    if (wg == 1) m_check(sc, epoch & 1);
    uint4 hv[12];
#pragma unroll
    for (int a = 0; a < 12; a++) asm volatile("" : "=r"(hv[a].x), "=r"(hv[a].y), "=r"(hv[a].z), "=r"(hv[a].w));

    constexpr uint32_t dWm = ((sbase + kOffWm) >> 4) | (1u << 16);
    constexpr uint32_t dWv = ((sbase + kOffWv) >> 4) | (1u << 16);
    const float cs = 0.07216878364870322f * 1.4426950408889634f;
    if (wg == 2) {
        asm volatile("bar.sync 13, 128;" ::: "memory");
        v_check(sc, epoch & 1);
    }
    mbar_wait(bar_x(wg, 0), 0);

    uint32_t st = (uint32_t)(wg * G + blockIdx.x) << 17 | kFirst | kPhase | (wg == 0 ? kSolo | kVeryFirst : 0);

    while (true) {
        float acc[96];
        uint32_t fa[48];
        const uint32_t dX = ((sbase + kOffX + wg_uniform() * kXBytes) >> 4) | (1u << 16);
        uint32_t ticket = 0;
        uint32_t lnk = baton_wait(st, 0);
        while (true) {
            const bool very_first = st & kVeryFirst;
            Gemm1<11>::run(acc, dX, dWm, very_first, st);
            wg_commit();
            if (!very_first) { baton_pass(lnk, st); break; }
            __syncwarp();
            if (m_agree(1)) break;
            wg_wait0();
            asm volatile("bar.arrive 7, 256;" ::: "memory");
            st ^= kRound;
        }
        draw_ticket(ticket);
        if (!(st & kFirst)) {
            const uint32_t w4 = warp4_uniform();
            const uint32_t slot = sbase + kOffStage + w4 * 2048;
            const int col = (st_out(st) & 63) * 8, row = (st_out(st) >> 6) * 8 + 2 * w4;
            store_round<0>(hv, slot, tmo.m, col, row);
            bulk_wait_read();
            __syncwarp();
            store_round<1>(hv, slot, tmo.m, col, row);
            bulk_wait_read();
            __syncwarp();
            store_round<2>(hv, slot, tmo.m, col, row);
        }
        static_assert(kPfInit == 2, "one start-up prefetch in the prologue, one here");
        if ((st & kFirst) && tid_now() == 128) prefetch_x(&tmp, (kNWG + (tid_now() >> 7)) * gridDim.x + blockIdx.x);
        __syncwarp();
        wg_wait0();
        fence_regs(acc);
#pragma unroll
        for (int i = 0; i < 48; i++) fa[i] = pack_bf16(acc[2 * i], acc[2 * i + 1]);

        float s[32];
        fence_regs(fa);
        if (!(st & kFirst) && (tid_now() & 127) == 0) publish(ticket);
        uint32_t pub, marks;
        lnk = baton_wait_pub(st, fa[47], pub);
        asm volatile("ld.volatile.shared.u32 %0, [%1];" : "=r"(marks) : "r"(kMarks) : "memory");
        wg_fence();
        Gemm2<11>::run(s, fa, dX, lnk, st);
        wg_commit();
        if ((st & kFirst) && (tid_now() & 127) == 0) publish(ticket);
        __syncwarp();
        const uint32_t alone = __reduce_or_sync(0xffffffffu, pub >= kNWin && (marks | 1u << 8 * (tid_now() >> 7)) == 0x10101);
        wg_wait0();
        fence_regs(s);
        fence_regs(fa);

        uint32_t pa[16];
        {
            float a0[8], a1[8];
#pragma unroll
            for (int j = 0; j < 8; j++) { a0[j] = fmaxf(s[4 * j], s[4 * j + 1]); a1[j] = fmaxf(s[4 * j + 2], s[4 * j + 3]); }
#pragma unroll
            for (int d = 4; d > 0; d >>= 1)
#pragma unroll
                for (int j = 0; j < d; j++) { a0[j] = fmaxf(a0[j], a0[j + d]); a1[j] = fmaxf(a1[j], a1[j + d]); }
            float m0 = a0[0], m1 = a1[0];
            m0 = fmaxf(m0, __shfl_xor_sync(0xffffffffu, m0, 1));
            m1 = fmaxf(m1, __shfl_xor_sync(0xffffffffu, m1, 1));
            m0 = fmaxf(m0, __shfl_xor_sync(0xffffffffu, m0, 2));
            m1 = fmaxf(m1, __shfl_xor_sync(0xffffffffu, m1, 2));
            m0 *= cs; m1 *= cs;
            float l0 = 0.f, l1 = 0.f;
#pragma unroll
            for (int j = 0; j < 8; j++) {
                s[4 * j]     = ex2(fmaf(s[4 * j], cs, -m0));
                s[4 * j + 1] = ex2(fmaf(s[4 * j + 1], cs, -m0));
                s[4 * j + 2] = ex2(fmaf(s[4 * j + 2], cs, -m1));
                s[4 * j + 3] = ex2(fmaf(s[4 * j + 3], cs, -m1));
                l0 += s[4 * j] + s[4 * j + 1];
                l1 += s[4 * j + 2] + s[4 * j + 3];
            }
            l0 += __shfl_xor_sync(0xffffffffu, l0, 1);
            l1 += __shfl_xor_sync(0xffffffffu, l1, 1);
            l0 += __shfl_xor_sync(0xffffffffu, l0, 2);
            l1 += __shfl_xor_sync(0xffffffffu, l1, 2);
            const float r0 = rcp(l0), r1 = rcp(l1);
#pragma unroll
            for (int j = 0; j < 8; j++) {
                pa[2 * j]     = pack_bf16(s[4 * j] * r0, s[4 * j + 1] * r0);
                pa[2 * j + 1] = pack_bf16(s[4 * j + 2] * r1, s[4 * j + 3] * r1);
            }
        }

        fence_regs(pa);
        if (alone) {
            finish_alone(pa, dX + (((8192u >> 4) - 1) << 16), dWv, tmo.m, st);
            return;
        }
        lnk = baton_wait_pub(st, pa[15], pub);
        if ((st & kFirst) && tid_now() == 0) set_link(1, 10);
        wg_fence();
        Gemm3<3>::run(acc, pa, dX + (((8192u >> 4) - 1) << 16));
        wg_commit();
        asm volatile("{\n.reg .pred p;\nsetp.ge.u32 p, %0, %1;\n@p st.volatile.shared.u8 [%2], %3;\n}\n"
                     ::"r"(pub), "n"(kNWin), "r"(kMarks + (tid_now() >> 7)), "r"(1) : "memory");
        baton_pass(lnk, st);
        const int nxt = (int)__reduce_or_sync(0xffffffffu, pub);
        wg_wait0();
        fence_regs(acc);
        fence_regs(pa);

        if (((tid_now() >> 5) & 3) == 0 && nxt < kNWin) {
            asm volatile("bar.sync %0, 128;" ::"r"((tid_now() >> 7) + 1) : "memory");
            if (elect_one()) {
                const uint32_t wgl = tid_now() >> 7;
                const uint32_t bar = sbase + kOffBar + 8 * wgl;
                mbar_expect_tx(bar, kXBytes);
                tma_load_x(sbase + kOffX + wgl * kXBytes, &tmx, bar, nxt);
            }
            __syncwarp();
        } else {
            asm volatile("bar.arrive %0, 128;" ::"r"((tid_now() >> 7) + 1) : "memory");
        }
#pragma unroll
        for (int i = 0; i < 48; i++) fa[i] = pack_bf16(acc[2 * i], acc[2 * i + 1]);

        asm volatile("st.volatile.shared.v4.b32 [%4], {%0, %1, %2, %3};"
                     :: "r"(fa[44]), "r"(fa[45]), "r"(fa[46]), "r"(fa[47]), "r"(sbase + kOffStash + (tid_now() & 127) * 16) : "memory");
        fence_regs(fa);
        if (((tid_now() >> 5) & 3) == 0 && nxt + kPfMin < kNWin) {
            if (elect_one()) {
                const int base = kNWG * (int)gridDim.x, t = nxt - base;
                const int hi = min(nxt + pf_lead(t), kNWin - 1);
                int lo = max(max(nxt - 1 + pf_lead(t - 1), nxt) + 1, base + kPfInit * (int)gridDim.x);
#pragma unroll 1
                for (; lo <= hi; lo++) prefetch_x(&tmp, lo);
            }
            __syncwarp();
        }
        if (nxt >= kNWin) {
            finish_last(fa, dWv, tmo.m, st);
            return;
        }
        lnk = baton_wait(st, fa[43]);
        wg_fence();
        Gemm4<0, 1>::run(acc, fa, dWv);
        wg_commit();
        Gemm4<2, 10>::run(acc, fa, dWv);
        wg_commit();
        wg_wait1();
        uint32_t fl[4];
        asm volatile("ld.volatile.shared.v4.b32 {%0, %1, %2, %3}, [%4];"
                     : "=r"(fl[0]), "=r"(fl[1]), "=r"(fl[2]), "=r"(fl[3]) : "r"(sbase + kOffStash + (tid_now() & 127) * 16) : "memory");
        wg_fence();
        wg192_rs<false, 0, koff(11, 24576)>(acc, fl, dWv);
        wg_commit();
        baton_pass(lnk, st);
        st = ((st ^ kPhase) & (kPhase | kSolo)) | st_win(st) << 4 | nxt << 17;
        uint32_t landed;
        asm volatile("{\n.reg .pred p;\nmbarrier.test_wait.parity.shared::cta.b64 p, [%1], %2;\nselp.b32 %0, 1, 0, p;\n}\n"
                     : "=r"(landed) : "r"(sbase + kOffBar + 8 * (tid_now() >> 7)), "r"(st & kPhase) : "memory");
        wg_wait0();
        fence_regs(acc);
        fence_regs(fa);
        fence_regs(fl);

#pragma unroll
        for (int a = 0; a < 6; a++)
#pragma unroll
            for (int r = 0; r < 2; r++)
                hv[2 * a + r] = make_uint4(pack_bf16(acc[16 * a + 2 * r], acc[16 * a + 2 * r + 1]), pack_bf16(acc[16 * a + 2 * r + 4], acc[16 * a + 2 * r + 5]),
                                           pack_bf16(acc[16 * a + 2 * r + 8], acc[16 * a + 2 * r + 9]), pack_bf16(acc[16 * a + 2 * r + 12], acc[16 * a + 2 * r + 13]));
        if (!landed) mbar_wait(sbase + kOffBar + 8 * (tid_now() >> 7), st & kPhase);
    }
}

typedef CUresult (*EncodeTiledFn)(CUtensorMap*, CUtensorMapDataType, cuuint32_t, void*, const cuuint64_t*,
                                  const cuuint64_t*, const cuuint32_t*, const cuuint32_t*, CUtensorMapInterleave,
                                  CUtensorMapSwizzle, CUtensorMapL2promotion, CUtensorMapFloatOOBfill);

}

extern "C" void kernel_launch(void* const* d_in, const int* in_sizes, int n_in, void* d_out, int out_size) {
    (void)in_sizes; (void)n_in; (void)out_size;
    const __nv_bfloat16* x    = (const __nv_bfloat16*)d_in[0];
    const __nv_bfloat16* wqkv = (const __nv_bfloat16*)d_in[1];
    const __nv_bfloat16* wo   = (const __nv_bfloat16*)d_in[2];

    static EncodeTiledFn encode = nullptr;
    static int num_sms = 0;
    static Scratch* scratch = nullptr;
    if (!encode) {
        void* fn = nullptr;
        cudaDriverEntryPointQueryResult qr;
        cudaGetDriverEntryPoint("cuTensorMapEncodeTiled", &fn, cudaEnableDefault, &qr);
        encode = (EncodeTiledFn)fn;
        cudaGetSymbolAddress((void**)&scratch, g_scratch);
        int dev = 0;
        cudaGetDevice(&dev);
        cudaDeviceGetAttribute(&num_sms, cudaDevAttrMultiProcessorCount, dev);
        cudaFuncSetAttribute(swin_attn_kernel, cudaFuncAttributeMaxDynamicSharedMemorySize, kSmemBytes);
    }
    CUtensorMap tmx;
    const cuuint64_t gdim[4] = {64, (cuuint64_t)kHW, (cuuint64_t)kHW, 3};
    const cuuint64_t gstr[3] = {(cuuint64_t)kC * 2, (cuuint64_t)kHW * kC * 2, 128};
    const cuuint32_t box[4] = {64, 8, 8, 3};
    const cuuint32_t estr[4] = {1, 1, 1, 1};
    encode(&tmx, CU_TENSOR_MAP_DATA_TYPE_BFLOAT16, 4, (void*)x, gdim, gstr, box, estr, CU_TENSOR_MAP_INTERLEAVE_NONE,
           CU_TENSOR_MAP_SWIZZLE_128B, CU_TENSOR_MAP_L2_PROMOTION_NONE, CU_TENSOR_MAP_FLOAT_OOB_FILL_NONE);

    CUtensorMap tmp;
    const cuuint64_t pdim[3] = {(cuuint64_t)kC, (cuuint64_t)kHW, (cuuint64_t)kHW};
    const cuuint64_t pstr[2] = {(cuuint64_t)kC * 2, (cuuint64_t)kHW * kC * 2};
    const cuuint32_t pbox[3] = {(cuuint32_t)kC, 8, 8};
    encode(&tmp, CU_TENSOR_MAP_DATA_TYPE_BFLOAT16, 3, (void*)x, pdim, pstr, pbox, estr, CU_TENSOR_MAP_INTERLEAVE_NONE,
           CU_TENSOR_MAP_SWIZZLE_NONE, CU_TENSOR_MAP_L2_PROMOTION_NONE, CU_TENSOR_MAP_FLOAT_OOB_FILL_NONE);
    CUtensorMap tmc;
    const cuuint32_t boxc[4] = {64, 8, 8, 1};
    encode(&tmc, CU_TENSOR_MAP_DATA_TYPE_BFLOAT16, 4, (void*)x, gdim, gstr, boxc, estr, CU_TENSOR_MAP_INTERLEAVE_NONE,
           CU_TENSOR_MAP_SWIZZLE_128B, CU_TENSOR_MAP_L2_PROMOTION_NONE, CU_TENSOR_MAP_FLOAT_OOB_FILL_NONE);
    OutMaps tmo;
    const cuuint32_t boxo[4] = {64, 8, 1, 2};
    encode(&tmo.m[0], CU_TENSOR_MAP_DATA_TYPE_BFLOAT16, 4, d_out, gdim, gstr, boxo, estr, CU_TENSOR_MAP_INTERLEAVE_NONE,
           CU_TENSOR_MAP_SWIZZLE_128B, CU_TENSOR_MAP_L2_PROMOTION_NONE, CU_TENSOR_MAP_FLOAT_OOB_FILL_NONE);
    const cuuint64_t odim[4] = {64, (cuuint64_t)kHW, (cuuint64_t)kHW, 2};
    const cuuint64_t ostr[3] = {(cuuint64_t)kC * 2, (cuuint64_t)kHW * kC * 2, (cuuint64_t)kHW * kC * 2 - 256};
    encode(&tmo.m[1], CU_TENSOR_MAP_DATA_TYPE_BFLOAT16, 4, (char*)d_out + 256, odim, ostr, boxo, estr, CU_TENSOR_MAP_INTERLEAVE_NONE,
           CU_TENSOR_MAP_SWIZZLE_128B, CU_TENSOR_MAP_L2_PROMOTION_NONE, CU_TENSOR_MAP_FLOAT_OOB_FILL_NONE);
    const cuuint32_t boxs[4] = {64, 8, 2, 1};
    encode(&tmo.m[2], CU_TENSOR_MAP_DATA_TYPE_BFLOAT16, 4, d_out, gdim, gstr, boxs, estr, CU_TENSOR_MAP_INTERLEAVE_NONE,
           CU_TENSOR_MAP_SWIZZLE_128B, CU_TENSOR_MAP_L2_PROMOTION_NONE, CU_TENSOR_MAP_FLOAT_OOB_FILL_NONE);
    swin_attn_kernel<<<num_sms, kThreads, kSmemBytes, cudaStreamPerThread>>>(wqkv, wo, scratch, d_out, tmo, tmx, tmp, tmc);
}
```

```cpp
#include <cuda_runtime.h>
#include <cuda_bf16.h>
#include <cuda.h>
#include <stdint.h>

namespace {

constexpr int kC      = 192;
constexpr int kHW     = 512;
constexpr int kNWin   = 4096;
constexpr int kXBytes = 64 * kC * 2;
constexpr int kWBytes = kC * kC * 2;
constexpr int kNWG    = 3;
constexpr int kThreads = kNWG * 128;
constexpr int kTiles  = 144;
constexpr int kPfInit = 2, kPfUp = 160, kPfPeak = 400, kPfHold = 800, kPfDown1 = 40, kPfBase2 = 300, kPfDown2 = 12, kPfMin = 140;
__device__ __forceinline__ int pf_lead(int t) {
    return min(min(kPfInit * (int)gridDim.x + ((t * kPfUp) >> 8), kPfPeak),
               max(max(kPfPeak - (((t - kPfHold) * kPfDown1) >> 8), kPfBase2 - ((t * kPfDown2) >> 8)), kPfMin));
}
constexpr int kEvictFrom = 3100;
constexpr int kPaceStart = 100, kPaceSpread = 500, kPaceStep0 = 750, kPaceMid = 2100, kPaceStep = 550;
constexpr uint32_t kMqkHint = 72;
constexpr uint32_t kPollDelay = 200;
constexpr uint32_t kWvoDelay = 1000;

constexpr int kOffWm  = 0;
constexpr int kOffWv  = kWBytes;
constexpr int kOffX   = 2 * kWBytes;
constexpr int kOffStage = kOffX + kNWG * kXBytes;
constexpr int kOffStash = kOffStage + 8192;
constexpr int kOffBar = kOffStash + 2048;
constexpr int kSmemBytes = kOffBar + 256;
constexpr uint32_t kSmemBase = 1024;

struct Scratch {
    uint32_t ticket[32];
    uint32_t epoch[32];
    uint32_t cnt_v[32];
    uint32_t cnt_m[32];
    uint4 img[2][2][kWBytes / 16];
};
__device__ __align__(128) Scratch g_scratch;

__device__ __forceinline__ uint32_t smem_u32(const void* p) { return (uint32_t)__cvta_generic_to_shared(p); }

__device__ __forceinline__ void mbar_init(uint32_t bar, uint32_t count) {
    asm volatile("mbarrier.init.shared::cta.b64 [%0], %1;" ::"r"(bar), "r"(count) : "memory");
}
__device__ __forceinline__ void mbar_expect_tx(uint32_t bar, uint32_t bytes) {
    asm volatile("mbarrier.arrive.expect_tx.shared::cta.b64 _, [%0], %1;" ::"r"(bar), "r"(bytes) : "memory");
}
__device__ __forceinline__ void mbar_wait(uint32_t bar, uint32_t parity) {
    uint32_t ok;
    uint32_t spins = 0;
    do {
        asm volatile("{\n.reg .pred p;\n"
                     "mbarrier.try_wait.parity.shared::cta.b64 p, [%1], %2;\n"
                     "selp.b32 %0, 1, 0, p;\n}\n"
                     : "=r"(ok) : "r"(bar), "r"(parity) : "memory");
        if (++spins > (1u << 26)) __trap();
    } while (!ok);
}
__device__ __forceinline__ uint32_t tid_now() {
    uint32_t t;
    asm volatile("mov.u32 %0, %%tid.x;" : "=r"(t));
    return t;
}
__device__ __forceinline__ bool elect_one() {
    uint32_t pred;
    asm volatile("{\n.reg .pred p;\nelect.sync _|p, 0xffffffff;\nselp.b32 %0, 1, 0, p;\n}\n" : "=r"(pred));
    return pred != 0;
}
__device__ __forceinline__ uint32_t wg_uniform() { return __reduce_or_sync(0xffffffffu, tid_now() >> 7); }
constexpr uint32_t kLink = kSmemBase + kOffBar + 64;
constexpr uint32_t kMarks = kLink + 24;
constexpr uint32_t kPhase = 1;
constexpr uint32_t kSolo = 2;
constexpr uint32_t kFirst = 4;
constexpr uint32_t kRound = 8;
constexpr uint32_t kVeryFirst = 1u << 16;
__device__ __forceinline__ int st_out(uint32_t st) { return (st >> 4) & 0xfff; }
__device__ __forceinline__ int st_win(uint32_t st) { return st >> 17; }
__device__ __forceinline__ uint32_t baton_wait(uint32_t st, uint32_t packed) {
    if (packed == 0xffffffffu) __trap();
    if (!(st & kSolo)) asm volatile("bar.sync %0, 256;" ::"r"((tid_now() >> 7) + 8) : "memory");
    uint32_t lnk;
    asm volatile("ld.volatile.shared.u32 %0, [%1];" : "=r"(lnk) : "r"(kLink + 8 * (tid_now() >> 7)) : "memory");
    return lnk;
}
__device__ __forceinline__ uint32_t baton_wait_pub(uint32_t st, uint32_t packed, uint32_t& pub) {
    if (packed == 0xffffffffu) __trap();
    asm volatile("bar.sync %0, %1;" ::"r"((tid_now() >> 7) + 8), "r"(st & kSolo ? 128 : 256) : "memory");
    uint32_t lnk;
    asm volatile("ld.volatile.shared.v2.u32 {%0, %1}, [%2];" : "=r"(lnk), "=r"(pub) : "r"(kLink + 8 * (tid_now() >> 7)) : "memory");
    return lnk;
}
__device__ __forceinline__ void baton_pass(uint32_t lnk, uint32_t& st) {
    const bool other = lnk != (tid_now() >> 7) + 8;
    if (other) asm volatile("bar.arrive %0, 256;" ::"r"(lnk) : "memory");
    st = other ? st & ~kSolo : st | kSolo;
}
__device__ __forceinline__ void set_link(int w, uint32_t v) { asm volatile("st.volatile.shared.u32 [%0], %1;" ::"r"(kLink + 8 * w), "r"(v) : "memory"); }
constexpr uint64_t kPolNormal = 0x1000000000000000ull, kPolFirst = 0x12F0000000000000ull;
__device__ __forceinline__ void tma_load_x(uint32_t dst, const CUtensorMap* tm, uint32_t bar, int win) {
    const int wh = win >> 6, ww = win & 63;
    asm volatile("cp.async.bulk.tensor.4d.shared::cluster.global.mbarrier::complete_tx::bytes.L2::cache_hint"
                 " [%0], [%1, {%3, %4, %5, %6}], [%2], %7;"
                 ::"r"(dst), "l"(tm), "r"(bar), "r"(0), "r"(ww * 8), "r"(wh * 8), "r"(0), "l"(win >= kEvictFrom ? kPolFirst : kPolNormal) : "memory");
}
__device__ __forceinline__ void tma_load_x_chunk(uint32_t dst, const CUtensorMap* tm, uint32_t bar, int win, int chunk) {
    const int wh = win >> 6, ww = win & 63;
    asm volatile("cp.async.bulk.tensor.4d.shared::cluster.global.mbarrier::complete_tx::bytes"
                 " [%0], [%1, {%3, %4, %5, %6}], [%2];"
                 ::"r"(dst), "l"(tm), "r"(bar), "r"(0), "r"(ww * 8), "r"(wh * 8), "r"(chunk) : "memory");
}
__device__ __forceinline__ void bulk_load(uint32_t dst, const void* src, uint32_t bytes, uint32_t bar) {
    asm volatile("cp.async.bulk.shared::cluster.global.mbarrier::complete_tx::bytes [%0], [%1], %2, [%3];"
                 ::"r"(dst), "l"(src), "r"(bytes), "r"(bar) : "memory");
}

__device__ __forceinline__ void wg_fence()  { asm volatile("wgmma.fence.sync.aligned;" ::: "memory"); }
__device__ __forceinline__ void wg_commit() { asm volatile("wgmma.commit_group.sync.aligned;" ::: "memory"); }
__device__ __forceinline__ void wg_wait0()  { asm volatile("wgmma.wait_group.sync.aligned 0;" ::: "memory"); }
__device__ __forceinline__ void wg_wait1()  { asm volatile("wgmma.wait_group.sync.aligned 1;" ::: "memory"); }
__device__ __forceinline__ void wg_wait2()  { asm volatile("wgmma.wait_group.sync.aligned 2;" ::: "memory"); }

template <int N> __device__ __forceinline__ void fence_regs(float (&d)[N]) {
#pragma unroll
    for (int i = 0; i < N; i++) asm volatile("" : "+f"(d[i])::"memory");
}
template <int N> __device__ __forceinline__ void fence_regs(uint32_t (&d)[N]) {
#pragma unroll
    for (int i = 0; i < N; i++) asm volatile("" : "+r"(d[i])::"memory");
}

#define ACC8(c, d, i) c(d[i]), c(d[i + 1]), c(d[i + 2]), c(d[i + 3]), c(d[i + 4]), c(d[i + 5]), c(d[i + 6]), c(d[i + 7])
#define ACC32(c, d) ACC8(c, d, 0), ACC8(c, d, 8), ACC8(c, d, 16), ACC8(c, d, 24)
#define ACC96(c, d) ACC32(c, d), ACC8(c, d, 32), ACC8(c, d, 40), ACC8(c, d, 48), ACC8(c, d, 56), \
                    ACC8(c, d, 64), ACC8(c, d, 72), ACC8(c, d, 80), ACC8(c, d, 88)
#define C_IO(x) "+f"(x)
#define C_O(x) "=f"(x)
#define REGS32 "{%0, %1, %2, %3, %4, %5, %6, %7, %8, %9, %10, %11, %12, %13, %14, %15, " \
               "%16, %17, %18, %19, %20, %21, %22, %23, %24, %25, %26, %27, %28, %29, %30, %31}"
#define REGS96 "{%0, %1, %2, %3, %4, %5, %6, %7, %8, %9, %10, %11, %12, %13, %14, %15, " \
               "%16, %17, %18, %19, %20, %21, %22, %23, %24, %25, %26, %27, %28, %29, %30, %31, " \
               "%32, %33, %34, %35, %36, %37, %38, %39, %40, %41, %42, %43, %44, %45, %46, %47, " \
               "%48, %49, %50, %51, %52, %53, %54, %55, %56, %57, %58, %59, %60, %61, %62, %63, " \
               "%64, %65, %66, %67, %68, %69, %70, %71, %72, %73, %74, %75, %76, %77, %78, %79, " \
               "%80, %81, %82, %83, %84, %85, %86, %87, %88, %89, %90, %91, %92, %93, %94, %95}"

#define DESC_HI "0x40000040"
#define MK_DESC(name, lo, off) "add.u32 t, " lo ", " off ";\nmov.b64 " name ", {t, " DESC_HI "};\n"

template <bool First, int OA, int OB> __device__ __forceinline__ void wg192_ss(float (&d)[96], uint32_t la, uint32_t lb) {
    if constexpr (First)
        asm volatile("{\n.reg .pred p;\n.reg .b32 t;\n.reg .b64 da, db;\nsetp.ne.b32 p, 0, 0;\n"
                     MK_DESC("da", "%96", "%98") MK_DESC("db", "%97", "%99")
                     "wgmma.mma_async.sync.aligned.m64n192k16.f32.bf16.bf16 " REGS96 ", da, db, p, 1, 1, 0, 0;\n}\n"
                     : ACC96(C_O, d) : "r"(la), "r"(lb), "n"(OA), "n"(OB));
    else
        asm volatile("{\n.reg .pred p;\n.reg .b32 t;\n.reg .b64 da, db;\nsetp.ne.b32 p, 1, 0;\n"
                     MK_DESC("da", "%96", "%98") MK_DESC("db", "%97", "%99")
                     "wgmma.mma_async.sync.aligned.m64n192k16.f32.bf16.bf16 " REGS96 ", da, db, p, 1, 1, 0, 0;\n}\n"
                     : ACC96(C_IO, d) : "r"(la), "r"(lb), "n"(OA), "n"(OB));
}
template <bool First, int TB, int OB> __device__ __forceinline__ void wg192_rs(float (&d)[96], const uint32_t* a, uint32_t lb) {
    if constexpr (First)
        asm volatile("{\n.reg .pred p;\n.reg .b32 t;\n.reg .b64 db;\nsetp.ne.b32 p, 0, 0;\n"
                     MK_DESC("db", "%100", "%102")
                     "wgmma.mma_async.sync.aligned.m64n192k16.f32.bf16.bf16 " REGS96 ", {%96, %97, %98, %99}, db, p, 1, 1, %101;\n}\n"
                     : ACC96(C_O, d) : "r"(a[0]), "r"(a[1]), "r"(a[2]), "r"(a[3]), "r"(lb), "n"(TB), "n"(OB));
    else
        asm volatile("{\n.reg .pred p;\n.reg .b32 t;\n.reg .b64 db;\nsetp.ne.b32 p, 1, 0;\n"
                     MK_DESC("db", "%100", "%102")
                     "wgmma.mma_async.sync.aligned.m64n192k16.f32.bf16.bf16 " REGS96 ", {%96, %97, %98, %99}, db, p, 1, 1, %101;\n}\n"
                     : ACC96(C_IO, d) : "r"(a[0]), "r"(a[1]), "r"(a[2]), "r"(a[3]), "r"(lb), "n"(TB), "n"(OB));
}
template <bool First, int TB, int OB> __device__ __forceinline__ void wg64_rs(float (&d)[32], const uint32_t* a, uint32_t lb) {
    if constexpr (First)
        asm volatile("{\n.reg .pred p;\n.reg .b32 t;\n.reg .b64 db;\nsetp.ne.b32 p, 0, 0;\n"
                     MK_DESC("db", "%36", "%38")
                     "wgmma.mma_async.sync.aligned.m64n64k16.f32.bf16.bf16 " REGS32 ", {%32, %33, %34, %35}, db, p, 1, 1, %37;\n}\n"
                     : ACC32(C_O, d) : "r"(a[0]), "r"(a[1]), "r"(a[2]), "r"(a[3]), "r"(lb), "n"(TB), "n"(OB));
    else
        asm volatile("{\n.reg .pred p;\n.reg .b32 t;\n.reg .b64 db;\nsetp.ne.b32 p, 1, 0;\n"
                     MK_DESC("db", "%36", "%38")
                     "wgmma.mma_async.sync.aligned.m64n64k16.f32.bf16.bf16 " REGS32 ", {%32, %33, %34, %35}, db, p, 1, 1, %37;\n}\n"
                     : ACC32(C_IO, d) : "r"(a[0]), "r"(a[1]), "r"(a[2]), "r"(a[3]), "r"(lb), "n"(TB), "n"(OB));
}
template <int OB> __device__ __forceinline__ void wg64_rs_reuse(float (&d)[32], const uint32_t* a, uint32_t lb, uint32_t one) {
    asm volatile("{\n.reg .pred p;\n.reg .b32 t;\n.reg .b64 db;\nsetp.ne.b32 p, %38, 1;\n"
                 MK_DESC("db", "%36", "%37")
                 "wgmma.mma_async.sync.aligned.m64n64k16.f32.bf16.bf16 " REGS32 ", {%32, %33, %34, %35}, db, p, 1, 1, 0;\n}\n"
                 : ACC32(C_IO, d) : "r"(a[0]), "r"(a[1]), "r"(a[2]), "r"(a[3]), "r"(lb), "n"(OB), "r"(one));
}
__host__ __device__ constexpr int koff(int kk, int chunk) { return ((kk >> 2) * chunk + (kk & 3) * 32) >> 4; }

__device__ __forceinline__ void stsm4(uint32_t addr, const uint4& v) {
    asm volatile("stmatrix.sync.aligned.m8n8.x4.shared.b16 [%0], {%1, %2, %3, %4};" ::"r"(addr), "r"(v.x), "r"(v.y), "r"(v.z), "r"(v.w) : "memory");
}
__device__ __forceinline__ void bulk_wait_read() {
    asm volatile("cp.async.bulk.wait_group.read 0;" ::: "memory");
}
__device__ __forceinline__ uint32_t stage_addr(uint32_t slot, uint32_t l) { return slot + (l & 7) * 128 + ((((l >> 3) & 3) ^ (l & 7)) << 4); }
__device__ __forceinline__ void stage_fence() {
    asm volatile("fence.proxy.async.shared::cta;" ::: "memory");
    __syncwarp();
}
template <int R> __device__ __forceinline__ void store_round(const uint4 (&h)[12], uint32_t slot, const CUtensorMap* tm, int col, int row) {
    const uint32_t sa = stage_addr(slot, tid_now());
#pragma unroll
    for (int i = 0; i < 2; i++) {
        const int r = (2 * R + i) / 3, c = (2 * R + i) % 3;
        stsm4(sa + i * 1024, h[4 * c + r]);
        stsm4((sa ^ 64) + i * 1024, h[4 * c + 2 + r]);
    }
    stage_fence();
    asm volatile("{\n.reg .pred p;\nelect.sync _|p, 0xffffffff;\n"
                 "@p cp.async.bulk.tensor.4d.global.shared::cta.bulk_group [%0, {%2, %3, %4, %5}], [%1];\n"
                 "@p cp.async.bulk.commit_group;\n}\n"
                 ::"l"(tm + (R == 1)), "r"(slot), "r"(0), "r"(col), "r"(row + (R == 2)), "r"((int)(R == 2)) : "memory");
}
__device__ __forceinline__ uint32_t warp4_uniform() { return __reduce_or_sync(0xffffffffu, (tid_now() >> 5) & 3); }
struct OutMaps { CUtensorMap m[3]; };
__host__ __device__ constexpr uint32_t bar_m(int c) { return kSmemBase + kOffBar + 32 + 8 * c; }
__device__ __forceinline__ void m_load(const Scratch* sc, int c, uint32_t par) {
    mbar_expect_tx(bar_m(c), 24576);
    bulk_load(kSmemBase + kOffWm + c * 24576, sc->img[par][0] + c * 1536, 24576, bar_m(c));
}
__device__ __forceinline__ bool m_agree(uint32_t ok) {
    uint32_t all;
    asm volatile("{\n.reg .pred p, q;\nsetp.ne.u32 p, %1, 0;\nbar.red.and.pred q, 7, 256, p;\nselp.b32 %0, 1, 0, q;\n}\n" : "=r"(all) : "r"(ok) : "memory");
    return all != 0;
}
__device__ __forceinline__ void m_check(const Scratch* sc, uint32_t par) {
    for (uint32_t round = 0;; round++) {
        uint32_t m = ~0u;
#pragma unroll 1
        for (int c = 0; c < 3; c++) {
            mbar_wait(bar_m(c), round & 1);
#pragma unroll
            for (int j = 0; j < 6; j++) {
                uint32_t v;
                asm volatile("ld.volatile.shared.b32 %0, [%1];" : "=r"(v)
                             : "r"(kSmemBase + kOffWm + c * 24576 + 4096 * j + (tid_now() & 127) * 32 + (tid_now() & 28)) : "memory");
                m = min(m, v);
            }
        }
        if (m_agree(m)) break;
        asm volatile("bar.sync 7, 256;" ::: "memory");
        if (round > (1u << 20)) __trap();
        if (tid_now() == 128) {
            m_load(sc, 0, par); m_load(sc, 1, par); m_load(sc, 2, par);
        }
    }
}
constexpr uint32_t kBarV = kSmemBase + kOffBar + 56;
__device__ __forceinline__ void v_load(const Scratch* sc, uint32_t par) {
    mbar_expect_tx(kBarV, kWBytes);
#pragma unroll 1
    for (int c = 0; c < 3; c++) bulk_load(kSmemBase + kOffWv + c * 24576, sc->img[par][1] + c * 1536, 24576, kBarV);
}
__device__ __forceinline__ void v_check(const Scratch* sc, uint32_t par) {
    for (uint32_t round = 0;; round++) {
        mbar_wait(kBarV, round & 1);
        uint32_t m = ~0u;
#pragma unroll
        for (int j = 0; j < 18; j++) {
            uint32_t v;
            asm volatile("ld.volatile.shared.b32 %0, [%1];" : "=r"(v)
                         : "r"(kSmemBase + kOffWv + 4096 * j + (tid_now() & 127) * 32 + (tid_now() & 28)) : "memory");
            m = min(m, v);
        }
        uint32_t all;
        asm volatile("{\n.reg .pred p, q;\nsetp.ne.u32 p, %1, 0;\nbar.red.and.pred q, 14, 128, p;\nselp.b32 %0, 1, 0, q;\n}\n" : "=r"(all) : "r"(m) : "memory");
        if (all) break;
        if (round > (1u << 20)) __trap();
        if (tid_now() == 352) v_load(sc, par);
    }
}
__host__ __device__ constexpr uint32_t bar_x(int w, int c) { return kSmemBase + kOffBar + 128 + 32 * w + 8 * c; }
template <int K> struct Gemm1 {
    static __device__ __forceinline__ void run(float (&d)[96], uint32_t lx, uint32_t lw, bool very_first, uint32_t st) {
        if constexpr (K > 0) Gemm1<K - 1>::run(d, lx, lw, very_first, st);
        if constexpr (K == 0 || K == 4 || K == 8) {
            if constexpr (K == 0) {
                if (very_first) mbar_wait(bar_m(0), (st & kRound) != 0);
            } else if (st & kFirst) {
                mbar_wait(bar_x(0, K / 4) + 32 * (tid_now() >> 7), 0);
                if (very_first) mbar_wait(bar_m(K / 4), (st & kRound) != 0);
            }
            wg_fence();
        }
        wg192_ss<K == 0, koff(K, 8192), koff(K, 24576)>(d, lx, lw);
    }
};
constexpr uint32_t kScAddr = kSmemBase + kOffBar + 96;
__device__ __forceinline__ void draw_ticket(uint32_t& ticket) {
    asm volatile("{\n.reg .pred p;\n.reg .b64 a;\nsetp.eq.u32 p, %1, 0;\nld.volatile.shared.u64 a, [%3];\n"
                 "@p atom.relaxed.gpu.global.inc.u32 %0, [a], %2;\n}\n"
                 : "+r"(ticket) : "r"(tid_now() & 127), "n"(kNWin - 1), "r"(kScAddr) : "memory");
}
template <int KK> struct Gemm2 { static __device__ __forceinline__ void run(float (&d)[32], const uint32_t* a, uint32_t lx, uint32_t lnk, uint32_t& st) {
    Gemm2<KK - 1>::run(d, a, lx, lnk, st); wg64_rs<KK == 0, 0, koff(KK, 8192)>(d, a + 4 * KK, lx);
    if constexpr (KK == 9) {
        __syncwarp();
        bulk_wait_read();
        baton_pass(lnk, st);
    } } };
template <> struct Gemm2<-1> { static __device__ __forceinline__ void run(float (&)[32], const uint32_t*, uint32_t, uint32_t, uint32_t&) {} };
template <int KK> struct Gemm3 { static __device__ __forceinline__ void run(float (&d)[96], const uint32_t* a, uint32_t lxt) {
    Gemm3<KK - 1>::run(d, a, lxt); wg192_rs<KK == 0, 1, KK * (2048 >> 4)>(d, a + 4 * KK, lxt); } };
template <> struct Gemm3<-1> { static __device__ __forceinline__ void run(float (&)[96], const uint32_t*, uint32_t) {} };
template <int K0, int KK> struct Gemm4 { static __device__ __forceinline__ void run(float (&d)[96], const uint32_t* a, uint32_t lw) {
    if constexpr (KK > K0) Gemm4<K0, KK - 1>::run(d, a, lw);
    wg192_rs<KK == 0, 0, koff(KK, 24576)>(d, a + 4 * KK, lw); } };

template <int C, int KK> struct Gemm3s { static __device__ __forceinline__ void run(float (&d)[32], const uint32_t* a, uint32_t lxt) {
    if constexpr (KK > 0) Gemm3s<C, KK - 1>::run(d, a, lxt);
    wg64_rs<KK == 0, 1, (C * 8192 + KK * 2048) / 16>(d, a + 4 * KK, lxt); } };
template <int C, int K0, int KK> struct Gemm4s { static __device__ __forceinline__ void run(float (&d)[32], const uint32_t* a, uint32_t lw, uint32_t one) {
    if constexpr (KK > K0) Gemm4s<C, K0, KK - 1>::run(d, a, lw, one);
    if constexpr (KK == 0) wg64_rs_reuse<C * 8192 / 16>(d, a, lw, one);
    else wg64_rs<false, 0, koff(KK, 24576) + C * 8192 / 16>(d, a + 4 * KK, lw); } };

__device__ __forceinline__ uint32_t pack_bf16(float lo, float hi) {
    uint32_t r;
    asm("cvt.rn.bf16x2.f32 %0, %1, %2;" : "=r"(r) : "f"(hi), "f"(lo));
    return r;
}
__device__ __forceinline__ float ex2(float x) {
    float r;
    asm("ex2.approx.ftz.f32 %0, %1;" : "=f"(r) : "f"(x));
    return r;
}
__device__ __forceinline__ float rcp(float x) {
    float r;
    asm("rcp.approx.ftz.f32 %0, %1;" : "=f"(r) : "f"(x));
    return r;
}
__device__ __forceinline__ void mma16816(float (&c)[4], uint32_t a0, uint32_t a1, uint32_t a2, uint32_t a3,
                                         uint32_t b0, uint32_t b1) {
    asm volatile("mma.sync.aligned.m16n8k16.row.col.f32.bf16.bf16.f32 {%0,%1,%2,%3}, {%4,%5,%6,%7}, {%8,%9}, {%0,%1,%2,%3};"
                 : "+f"(c[0]), "+f"(c[1]), "+f"(c[2]), "+f"(c[3])
                 : "r"(a0), "r"(a1), "r"(a2), "r"(a3), "r"(b0), "r"(b1));
}

struct FoldRegs { uint4 B0[6], B1[6]; uint32_t A[48]; };

__device__ __forceinline__ void st_relaxed64(void* p, uint32_t a, uint32_t b, uint32_t on) {
    asm volatile("{\n.reg .pred q;\nsetp.ne.u32 q, %3, 0;\n@q st.relaxed.gpu.global.v2.b32 [%0], {%1, %2};\n}\n" ::"l"(p), "r"(a), "r"(b), "r"(on) : "memory");
}
__device__ __forceinline__ uint32_t pack_nonzero(float lo, float hi) { const uint32_t v = pack_bf16(lo, hi); return v != 0 ? v : 0x80000000u; }
__device__ __forceinline__ void fold_store(char* img, uint32_t* cnt, uint32_t epoch, uint32_t on, int n_lo, int n_hi, int k0, int lane, const float (&c0)[4], const float (&c1)[4]) {
    const int q = lane & 3;
    const int u = ((k0 & 63) >> 3) + (q >> 1);
    const int base = (k0 >> 6) * 24576 + (q & 1) * 8;
    char* p_lo = img + (base + n_lo * 128 + ((u ^ (n_lo & 7)) << 4));
    char* p_hi = img + (base + n_hi * 128 + ((u ^ (n_hi & 7)) << 4));
    const uint32_t v0 = pack_nonzero(c0[0], c0[1]);
    const uint32_t par = (epoch & 1) | (v0 & (gridDim.y - 1));
    st_relaxed64(p_lo + par * (2 * kWBytes), v0, pack_nonzero(c1[0], c1[1]), on);
    st_relaxed64(p_hi + par * (2 * kWBytes), pack_nonzero(c0[2], c0[3]), pack_nonzero(c1[2], c1[3]), on);
    asm volatile("{\n.reg .pred q;\nsetp.ne.u32 q, %1, 0;\n@q red.relaxed.gpu.global.inc.u32 [%0], 0xffffffff;\n}\n" ::"l"(cnt), "r"(lane == 0 ? on : 0u) : "memory");
    st_relaxed64(p_lo + (par ^ 1) * (2 * kWBytes), 0, 0, on);
    st_relaxed64(p_hi + (par ^ 1) * (2 * kWBytes), 0, 0, on);
}
__device__ __forceinline__ void fold_load_qk(FoldRegs& r, const __nv_bfloat16* __restrict__ wqkv, int tile, int lane) {
    const int g = lane >> 2, q = lane & 3;
    const int n0 = (tile / 12) * 16, k0 = (tile % 12) * 16;
    const int kb = k0 + 4 * (g >> 1) + (g & 1);
    const uint4* pa0 = reinterpret_cast<const uint4*>(wqkv + (size_t)(n0 + g) * 576 + 192 + 8 * q);
    const uint4* pa1 = reinterpret_cast<const uint4*>(wqkv + (size_t)(n0 + g + 8) * 576 + 192 + 8 * q);
    const uint4* pb0 = reinterpret_cast<const uint4*>(wqkv + (size_t)kb * 576 + 8 * q);
    const uint4* pb1 = reinterpret_cast<const uint4*>(wqkv + (size_t)(kb + 2) * 576 + 8 * q);
#pragma unroll
    for (int j = 0; j < 6; j++) {
        const uint4 lo = __ldg(pa0 + 4 * j), hi = __ldg(pa1 + 4 * j);
        r.A[8 * j + 0] = lo.x; r.A[8 * j + 1] = hi.x; r.A[8 * j + 2] = lo.y; r.A[8 * j + 3] = hi.y;
        r.A[8 * j + 4] = lo.z; r.A[8 * j + 5] = hi.z; r.A[8 * j + 6] = lo.w; r.A[8 * j + 7] = hi.w;
        r.B0[j] = __ldg(pb0 + 4 * j);
        r.B1[j] = __ldg(pb1 + 4 * j);
    }
}
__device__ __forceinline__ void fold_load_vo(FoldRegs& r, const __nv_bfloat16* __restrict__ wqkv, const __nv_bfloat16* __restrict__ wo,
                                             int tile, int lane) {
    const int g = lane >> 2, q = lane & 3;
    const int ch0 = (tile / 12) * 16 + 2 * g;
    const int k0 = (tile % 12) * 16;
    const int kb = k0 + 4 * (g >> 1) + (g & 1);
    const uint4* pb0 = reinterpret_cast<const uint4*>(wqkv + (size_t)kb * 576 + 384 + 8 * q);
    const uint4* pb1 = reinterpret_cast<const uint4*>(wqkv + (size_t)(kb + 2) * 576 + 384 + 8 * q);
    const uint32_t* pw = reinterpret_cast<const uint32_t*>(wo + (size_t)(8 * q) * kC + ch0);
#pragma unroll
    for (int j = 0; j < 6; j++) {
        r.B0[j] = __ldg(pb0 + 4 * j);
        r.B1[j] = __ldg(pb1 + 4 * j);
#pragma unroll
        for (int i = 0; i < 8; i++) r.A[8 * j + i] = __ldg(pw + (32 * j + i) * (kC / 2));
    }
}
template <bool kVO>
__device__ __forceinline__ void fold_compute_store(FoldRegs& r, Scratch* sc, int tile, int lane, uint32_t epoch, uint32_t on) {
    const int g = lane >> 2;
    float c0[4] = {0.f, 0.f, 0.f, 0.f}, c1[4] = {0.f, 0.f, 0.f, 0.f}, c2[4] = {0.f, 0.f, 0.f, 0.f}, c3[4] = {0.f, 0.f, 0.f, 0.f};
#pragma unroll
    for (int j = 0; j < 6; j++) {
        uint32_t a[8];
        if constexpr (kVO) {
#pragma unroll
            for (int i = 0; i < 4; i++) {
                a[2 * i]     = __byte_perm(r.A[8 * j + 2 * i], r.A[8 * j + 2 * i + 1], 0x5410);
                a[2 * i + 1] = __byte_perm(r.A[8 * j + 2 * i], r.A[8 * j + 2 * i + 1], 0x7632);
            }
        } else {
#pragma unroll
            for (int i = 0; i < 8; i++) asm volatile("prmt.b32 %0, %1, 0, 0x3210;" : "=r"(a[i]) : "r"(r.A[8 * j + i]));
        }
        mma16816(c0, a[0], a[1], a[2], a[3], r.B0[j].x, r.B0[j].y);
        mma16816(c1, a[0], a[1], a[2], a[3], r.B1[j].x, r.B1[j].y);
        mma16816(c2, a[4], a[5], a[6], a[7], r.B0[j].z, r.B0[j].w);
        mma16816(c3, a[4], a[5], a[6], a[7], r.B1[j].z, r.B1[j].w);
    }
#pragma unroll
    for (int i = 0; i < 4; i++) { c0[i] += c2[i]; c1[i] += c3[i]; }
    const int k0 = (tile % 12) * 16;
    if constexpr (kVO) {
        const int n = (tile / 12) * 16 + 2 * g;
        fold_store(reinterpret_cast<char*>(sc->img[0][1]), sc->cnt_v, epoch, on, n, n + 1, k0, lane, c0, c1);
    } else {
        const int n0 = (tile / 12) * 16;
        fold_store(reinterpret_cast<char*>(sc->img[0][0]), sc->cnt_m, epoch, on, n0 + g, n0 + g + 8, k0, lane, c0, c1);
    }
}

__device__ __forceinline__ void prefetch_x(const CUtensorMap* tm, int win) {
    const int wh = win >> 6, ww = win & 63;
    asm volatile("cp.async.bulk.prefetch.tensor.3d.L2.global.tile [%0, {%1, %2, %3}];"
                 ::"l"(tm), "r"(0), "r"(ww * 8), "r"(wh * 8) : "memory");
}

__device__ __forceinline__ void publish(uint32_t ticket) {
    asm volatile("{\n.reg .pred p;\nsetp.eq.u32 p, %2, 0;\n@p st.volatile.shared.u32 [%0], %1;\n}\n"
                 ::"r"(kLink + 4 + 8 * (tid_now() >> 7)), "r"(ticket), "r"(tid_now() & 127) : "memory");
}
__device__ __forceinline__ void reset_for_next_launch() {
    Scratch* q;
    asm volatile("ld.volatile.shared.u64 %0, [%1];" : "=l"(q) : "r"(kScAddr) : "memory");
    q->cnt_v[0] = 0; q->cnt_m[0] = 0; atomicAdd(q->epoch, 1);
}

__device__ __forceinline__ void send_slice(const CUtensorMap* tm, uint32_t slot, uint32_t col, uint32_t row, uint32_t c) {
    stage_fence();
    asm volatile("{\n.reg .pred p;\nelect.sync _|p, 0xffffffff;\n"
                 "@p cp.async.bulk.tensor.4d.global.shared::cta.bulk_group [%0, {%2, %3, %4, %5}], [%1];\n}\n"
                 ::"l"(tm + 2), "r"(slot + c * 2048), "r"(0), "r"(col), "r"(row), "r"(c) : "memory");
}
__device__ __forceinline__ void bulk_commit() { asm volatile("cp.async.bulk.commit_group;" ::: "memory"); }
template <bool AddNz> __device__ __forceinline__ void pack_slice(uint4 (&h)[4], float (&o)[32], float nz) {
    fence_regs(o);
    auto pk = [&](int i) { return pack_bf16(o[i], AddNz ? o[i + 1] + nz : o[i + 1]); };
#pragma unroll
    for (int i = 0; i < 4; i++) {
        const int b = 16 * (i & 1) + 2 * (i >> 1);
        h[i] = make_uint4(pk(b), pk(b + 4), pk(b + 8), pk(b + 12));
    }
#pragma unroll
    for (int i = 0; i < 4; i++) asm volatile("" : "+r"(h[i].x), "+r"(h[i].y), "+r"(h[i].z), "+r"(h[i].w)::"memory");
}
__device__ __forceinline__ void stage_part(uint32_t sa, int c, const uint4 (&h)[4], int i) { stsm4((sa ^ (i & 1) * 64) + (i >> 1) * 1024 + c * 2048, h[i]); }
#define W(C, K0, K1, O) Gemm4s<C, K0, K1>::run(O, fa, dWv, one)
#define W_STAGE(C, O) stage_part(sa, C - 1, h, 0); W(C, 5, 5, O); stage_part(sa, C - 1, h, 1); W(C, 6, 6, O); \
                      stage_part(sa, C - 1, h, 2); W(C, 7, 7, O); stage_part(sa, C - 1, h, 3); W(C, 8, 8, O)

__device__ __forceinline__ void finish_alone(const uint32_t (&pa_in)[16], uint32_t dXt, uint32_t dWv, const CUtensorMap* tm, uint32_t st) {
    uint32_t pa[16];
#pragma unroll
    for (int j = 0; j < 16; j++) pa[j] = pa_in[j];
    char* out;
    asm volatile("ld.volatile.shared.u64 %0, [%1];" : "=l"(out) : "r"(kScAddr + 8) : "memory");
    const uint32_t one = gridDim.y;
    const float nz = __uint_as_float(one << 31);
    float u0[32], u1[32], u2[32];
    float (&o0)[32] = u0, (&o1)[32] = u2, (&o2)[32] = u0;
    uint32_t fa[48];
    uint4 h[4];
    auto pack_a = [&](float (&u)[32], int c) {
        fence_regs(u);
#pragma unroll
        for (int i = 0; i < 16; i++) {
            fa[16 * c + i] = pack_bf16(c != 1 ? u[2 * i] + nz : u[2 * i], u[2 * i + 1]);
            asm volatile("" : "+r"(fa[16 * c + i])::"memory");
        }
        wg_fence();
    };
    const uint32_t t = tid_now(), win = st_win(st);
    const uint32_t slot = kSmemBase + kOffX + (t >> 5) * 6144, sa = stage_addr(slot, t);
    const uint32_t col = (win & 63) * 8, row = (win >> 6) * 8 + ((t >> 4) & 6);
    if (!(st & kSolo)) asm volatile("bar.sync %0, 256;" ::"r"((t >> 7) + 8) : "memory");
    wg_fence();
    Gemm3s<0, 3>::run(u0, pa, dXt); wg_commit();
    Gemm3s<1, 3>::run(u1, pa, dXt); wg_commit();
    Gemm3s<2, 3>::run(u2, pa, dXt); wg_commit();
    wg_wait2(); pack_a(u0, 0);
    W(0, 0, 3, o0); wg_commit();
    wg_wait2(); pack_a(u1, 1);
    W(0, 4, 7, o0); wg_commit();
    wg_wait2(); pack_a(u2, 2);
    W(0, 8, 11, o0); wg_commit();
    W(1, 0, 0, o1);
    asm volatile("bar.sync %0, 128;" ::"r"((t >> 7) + 1) : "memory");
    wg_fence();
    W(1, 1, 4, o1); wg_commit();
    wg_wait1(); pack_slice<true>(h, o0, nz);
    W_STAGE(1, o1);
    W(1, 9, 10, o1);
    send_slice(tm, slot, col, row, 0);
    wg_fence();
    W(1, 11, 11, o1); wg_commit();
    W(2, 0, 4, o2); wg_commit();
    wg_wait1(); pack_slice<false>(h, o1, nz);
    W_STAGE(2, o2);
    W(2, 9, 10, o2);
    send_slice(tm, slot, col, row, 1);
    wg_fence();
    W(2, 11, 11, o2); wg_commit();
    __syncwarp();
    bulk_commit();
    __syncwarp();
    wg_wait0(); pack_slice<false>(h, o2, nz);
    fence_regs(fa);
#pragma unroll
    for (int i = 0; i < 4; i++) stage_part(sa, 2, h, i);
    __syncwarp();
    const uint32_t tok = (t >> 3) & 3, j = t & 7, la = slot + tok * 128 + ((j ^ tok) << 4);
    out += (row * kHW + col + tok) * (kC * 2) + j * 16 + 256;
#pragma unroll
    for (int i = 0; i < 4; i++)
        asm volatile("ld.volatile.shared.v4.b32 {%0, %1, %2, %3}, [%4];" : "=r"(h[i].x), "=r"(h[i].y), "=r"(h[i].z), "=r"(h[i].w)
                     : "r"((la ^ (i & 1) * 64) + i * 512 + 4096) : "memory");
#pragma unroll
    for (int i = 0; i < 4; i++)
        asm volatile("st.global.v4.b32 [%0], {%1, %2, %3, %4};"
                     ::"l"(out + ((i >> 1) * kHW + 4 * (i & 1)) * (kC * 2)), "r"(h[i].x), "r"(h[i].y), "r"(h[i].z), "r"(h[i].w) : "memory");
    __syncwarp();
    bulk_wait_read();
}

__device__ __forceinline__ void finish_last(const uint32_t (&fa_in)[48], uint32_t dWv, const CUtensorMap* tm, uint32_t st) {
    uint32_t fa[48];
#pragma unroll
    for (int j = 0; j < 48; j++) fa[j] = fa_in[j];
    const uint32_t one = gridDim.y;
    const float nz = __uint_as_float(one << 31);
    float o0[32], o1[32];
    float (&o2)[32] = o0;
    uint4 h[4];
    const uint32_t t = tid_now(), win = st_win(st);
    const uint32_t slot = kSmemBase + kOffX + (t >> 5) * 6144, sa = stage_addr(slot, t);
    const uint32_t col = (win & 63) * 8, row = (win >> 6) * 8 + ((t >> 4) & 6);
    const uint32_t la = kLink + 8 * min(t & 127, 2u), me = (t >> 7) + 8;
    uint32_t pub, l;
    const uint32_t lnk = baton_wait_pub(st, sa + la + col + row, pub);
    asm volatile("ld.volatile.shared.u32 %0, [%1];" : "=r"(l) : "r"(la) : "memory");
    wg_fence();
    wg64_rs<true, 0, 0>(o0, fa, dWv);
    W(0, 1, 3, o0);
    asm volatile("{\n.reg .pred p;\nsetp.eq.u32 p, %0, %1;\n@p st.volatile.shared.u32 [%2], %3;\n}\n" ::"r"(l), "r"(me), "r"(la), "r"(lnk) : "memory");
    W(0, 4, 11, o0); wg_commit();
    wg64_rs<true, 0, 8192 / 16>(o1, fa, dWv);
    W(1, 1, 4, o1); wg_commit();
    wg_wait1(); pack_slice<false>(h, o0, nz);
    W_STAGE(1, o1);
    W(1, 9, 10, o1);
    send_slice(tm, slot, col, row, 0);
    wg_fence();
    W(1, 11, 11, o1); wg_commit();
    W(2, 0, 4, o2); wg_commit();
    wg_wait1(); pack_slice<false>(h, o1, nz);
    W_STAGE(2, o2);
    W(2, 9, 9, o2);
    asm volatile("{\n.reg .pred p;\nsetp.ne.u32 p, %0, %1;\n@p bar.arrive %0, 256;\n}\n" ::"r"(lnk), "r"(me) : "memory");
    wg_fence();
    W(2, 10, 11, o2); wg_commit();
    send_slice(tm, slot, col, row, 1);
    wg_wait0(); pack_slice<true>(h, o2, nz);
    fence_regs(fa);
#pragma unroll
    for (int i = 0; i < 4; i++) stage_part(sa, 2, h, i);
    send_slice(tm, slot, col, row, 2);
    bulk_commit();
    bulk_wait_read();
}
#undef W
#undef W_STAGE

__global__ void __launch_bounds__(kThreads, 1)
swin_attn_kernel(const __nv_bfloat16* __restrict__ wqkv, const __nv_bfloat16* __restrict__ wo, Scratch* __restrict__ sc, void* out,
                 const __grid_constant__ OutMaps tmo, const __grid_constant__ CUtensorMap tmx, const __grid_constant__ CUtensorMap tmp, const __grid_constant__ CUtensorMap tmc) {
    extern __shared__ uint8_t smem_raw[];
    constexpr uint32_t sbase = kSmemBase;
    const int tid = threadIdx.x, lane = tid & 31;
    const int G = gridDim.x;

    FoldRegs fq;
#pragma unroll
    for (int j = 0; j < 6; j++) {
        asm volatile("" : "=r"(fq.B0[j].x), "=r"(fq.B0[j].y), "=r"(fq.B0[j].z), "=r"(fq.B0[j].w));
        asm volatile("" : "=r"(fq.B1[j].x), "=r"(fq.B1[j].y), "=r"(fq.B1[j].z), "=r"(fq.B1[j].w));
    }
#pragma unroll
    for (int j = 0; j < 48; j++) asm volatile("" : "=r"(fq.A[j]));
    uint32_t epoch;
    asm volatile("ld.relaxed.gpu.global.u32 %0, [%1];" : "=r"(epoch) : "l"(sc->epoch) : "memory");
    {
        const int t = blockIdx.x + (tid & 32 ? G : 0);
        if (tid < 64 && t < kTiles) fold_load_qk(fq, wqkv, t, lane);
    }
    __syncwarp();
    if (smem_u32(smem_raw) != kSmemBase) __trap();
    const uint32_t warpu = __reduce_or_sync(0xffffffffu, (uint32_t)tid >> 5), wgu = warpu >> 2;
    const int warp = (int)warpu, wg = (int)wgu;
    const int ftile = blockIdx.x + (warp & 1) * G;
    if (warp == 3) {
        const uint32_t i = blockIdx.x + G * (lane & 15);
        const char* p = lane < 16 ? (const char*)wo + i * 128 : (const char*)wqkv + i * 128 + (i / 3 + 1) * 768;
        if (i < 576) asm volatile("prefetch.global.L2 [%0];" ::"l"(p) : "memory");
    }
    if (warp == 10) {
        if (lane == 0) {
#pragma unroll
            for (int w = 0; w < kNWG; w++) {
                mbar_init(sbase + kOffBar + 8 * w, 1);
#pragma unroll
                for (int c = 0; c < 3; c++) mbar_init(bar_x(w, c), 1);
            }
            asm volatile("fence.mbarrier_init.release.cluster;" ::: "memory");
        }
        __syncwarp();
        asm volatile("bar.arrive 11, 384;" ::: "memory");
        if (lane == 0) {
            const uint32_t t0 = (uint32_t)clock64() + kPaceStart + ((blockIdx.x * 37) & 63) * kPaceSpread / 64;
#pragma unroll 1
            for (int i = 0; i <= 3 * kNWG; i++) {
                while ((int)((uint32_t)clock64() - t0) < (i < 3 ? i * kPaceStep0 : kPaceMid + (i - 3) * kPaceStep)) {}
                const int w = i / 3, c = i % 3;
                if (w < kNWG) {
                    mbar_expect_tx(bar_x(w, c), 8192);
                    tma_load_x_chunk(sbase + kOffX + w * kXBytes + c * 8192, &tmc, bar_x(w, c), w * G + blockIdx.x, c);
                } else {
                    prefetch_x(&tmp, kNWG * G + blockIdx.x);
                }
            }
        }
    }
    if (warp < 3) {
        for (int t = ftile;;) {
            const bool on = warp < 2 && t < kTiles;
            fold_compute_store<false>(fq, sc, t, lane, epoch, on);
            t += 2 * G;
            if (__builtin_expect(warp == 2 || t >= kTiles, 1)) break;
            fold_load_qk(fq, wqkv, t, lane);
        }
    }
    if (warp < 4) {
        asm volatile("bar.sync 11, 384;" ::: "memory");
    } else if (warp == 4) {
        if (lane == 0) {
            asm volatile("st.shared.v4.u32 [%0], {9, 0, 8, 0};\nst.shared.v4.u32 [%0 + 16], {8, 0, 0, 0};" ::"r"(kLink) : "memory");
            asm volatile("st.shared.v2.u64 [%0], {%1, %2};" ::"r"(kScAddr), "l"(sc), "l"(out) : "memory");
            mbar_init(bar_m(0), 1);
            mbar_init(bar_m(1), 1);
            mbar_init(bar_m(2), 1);
            asm volatile("fence.mbarrier_init.release.cluster;" ::: "memory");
        }
        __syncwarp();
        asm volatile("bar.arrive 12, 128;" ::: "memory");
        uint32_t v;
        asm volatile("ld.relaxed.gpu.global.u32 %0, [%1];" : "=r"(v) : "l"(sc->cnt_m) : "memory");
        asm volatile("bar.sync 11, 384;" ::: "memory");
        { const uint32_t t0 = (uint32_t)clock64(); while ((uint32_t)clock64() - t0 < kPollDelay) {} }
        if (lane == 0) {
            uint32_t spins = 0;
            while (v < kMqkHint) {
                asm volatile("ld.relaxed.gpu.global.u32 %0, [%1];" : "=r"(v) : "l"(sc->cnt_m) : "memory");
                if (++spins > (1u << 22)) __trap();
            }
            const uint32_t par = epoch & 1;
            m_load(sc, 0, par); m_load(sc, 1, par); m_load(sc, 2, par);
        }
    } else if (warp == 11) {
        if (lane == 0) {
            mbar_init(kBarV, 1);
            asm volatile("fence.mbarrier_init.release.cluster;" ::: "memory");
        }
        __syncwarp();
        asm volatile("bar.sync 11, 384;" ::: "memory");
        if (lane == 0) {
            uint32_t v, spins = 0;
            do {
                asm volatile("ld.relaxed.gpu.global.u32 %0, [%1];" : "=r"(v) : "l"(sc->cnt_v) : "memory");
                if (++spins > (1u << 22)) __trap();
            } while (v < kTiles);
            uint32_t ok = 0, n = 0;
            while (!ok && ++n < 64)
                asm volatile("{\n.reg .pred p;\nmbarrier.try_wait.parity.shared::cta.b64 p, [%1], 0;\nselp.b32 %0, 1, 0, p;\n}\n" : "=r"(ok) : "r"(bar_m(2)) : "memory");
            v_load(sc, epoch & 1);
        }
    } else if (warp == 10) {
    } else if (warp >= 8) {
        asm volatile("bar.arrive 11, 384;" ::: "memory");
        if (warp == 9) { const uint32_t t0 = (uint32_t)clock64(); while ((uint32_t)clock64() - t0 < kWvoDelay) {} }
        FoldRegs fr;
        for (int t = G - 1 - blockIdx.x + (warp & 1) * G; t < kTiles; t += 2 * G) {
            fold_load_vo(fr, wqkv, wo, t, lane);
            fold_compute_store<true>(fr, sc, t, lane, epoch, 1);
        }
    } else {
        asm volatile("bar.arrive 11, 384;" ::: "memory");
        if (lane == 0) asm volatile("prefetch.tensormap [%0];" ::"l"(warp == 5 ? &tmo.m[0] : warp == 6 ? &tmo.m[1] : &tmx) : "memory");
        if (lane == 0 && warp == 5) asm volatile("prefetch.tensormap [%0];" ::"l"(&tmo.m[2]) : "memory");
        asm volatile("bar.sync 12, 128;" ::: "memory");
    }
    __syncwarp();
    if (wg == 1) m_check(sc, epoch & 1);
    uint4 hv[12];
#pragma unroll
    for (int a = 0; a < 12; a++) asm volatile("" : "=r"(hv[a].x), "=r"(hv[a].y), "=r"(hv[a].z), "=r"(hv[a].w));

    constexpr uint32_t dWm = ((sbase + kOffWm) >> 4) | (1u << 16);
    constexpr uint32_t dWv = ((sbase + kOffWv) >> 4) | (1u << 16);
    const float cs = 0.07216878364870322f * 1.4426950408889634f;
    if (wg == 2) {
        asm volatile("bar.sync 13, 128;" ::: "memory");
        v_check(sc, epoch & 1);
    }
    mbar_wait(bar_x(wg, 0), 0);

    uint32_t st = (uint32_t)(wg * G + blockIdx.x) << 17 | kFirst | kPhase | (wg == 0 ? kSolo | kVeryFirst : 0);

    while (true) {
        float acc[96];
        uint32_t fa[48];
        const uint32_t dX = ((sbase + kOffX + wg_uniform() * kXBytes) >> 4) | (1u << 16);
        uint32_t ticket = 0;
        uint32_t lnk = baton_wait(st, 0);
        while (true) {
            const bool very_first = st & kVeryFirst;
            Gemm1<11>::run(acc, dX, dWm, very_first, st);
            wg_commit();
            if (!very_first) { baton_pass(lnk, st); break; }
            __syncwarp();
            if (m_agree(1)) break;
            wg_wait0();
            asm volatile("bar.arrive 7, 256;" ::: "memory");
            st ^= kRound;
        }
        draw_ticket(ticket);
        if (!(st & kFirst)) {
            const uint32_t w4 = warp4_uniform();
            const uint32_t slot = sbase + kOffStage + w4 * 2048;
            const int col = (st_out(st) & 63) * 8, row = (st_out(st) >> 6) * 8 + 2 * w4;
            store_round<0>(hv, slot, tmo.m, col, row);
            bulk_wait_read();
            __syncwarp();
            store_round<1>(hv, slot, tmo.m, col, row);
            bulk_wait_read();
            __syncwarp();
            store_round<2>(hv, slot, tmo.m, col, row);
        }
        static_assert(kPfInit == 2, "one start-up prefetch in the prologue, one here");
        if ((st & kFirst) && tid_now() == 128) prefetch_x(&tmp, (kNWG + (tid_now() >> 7)) * gridDim.x + blockIdx.x);
        __syncwarp();
        wg_wait0();
        fence_regs(acc);
#pragma unroll
        for (int i = 0; i < 48; i++) fa[i] = pack_bf16(acc[2 * i], acc[2 * i + 1]);

        float s[32];
        fence_regs(fa);
        if (!(st & kFirst)) publish(ticket);
        uint32_t pub, marks;
        lnk = baton_wait_pub(st, fa[47], pub);
        asm volatile("ld.volatile.shared.u32 %0, [%1];" : "=r"(marks) : "r"(kMarks) : "memory");
        wg_fence();
        Gemm2<11>::run(s, fa, dX, lnk, st);
        wg_commit();
        uint32_t mine = pub;
        if (st & kFirst) {
            publish(ticket);
            mine = ticket;
        }
        if (mine == kNWin - 1 && (tid_now() & 127) == 0) reset_for_next_launch();
        __syncwarp();
        const uint32_t alone = __reduce_or_sync(0xffffffffu, pub >= kNWin - kNWG * gridDim.x && ((marks | 1u << 8 * (tid_now() >> 7)) ^ (st & kFirst)) == 0x10101);
        wg_wait0();
        fence_regs(s);
        fence_regs(fa);

        uint32_t pa[16];
        {
            float a0[8], a1[8];
#pragma unroll
            for (int j = 0; j < 8; j++) { a0[j] = fmaxf(s[4 * j], s[4 * j + 1]); a1[j] = fmaxf(s[4 * j + 2], s[4 * j + 3]); }
#pragma unroll
            for (int d = 4; d > 0; d >>= 1)
#pragma unroll
                for (int j = 0; j < d; j++) { a0[j] = fmaxf(a0[j], a0[j + d]); a1[j] = fmaxf(a1[j], a1[j + d]); }
            float m0 = a0[0], m1 = a1[0];
            m0 = fmaxf(m0, __shfl_xor_sync(0xffffffffu, m0, 1));
            m1 = fmaxf(m1, __shfl_xor_sync(0xffffffffu, m1, 1));
            m0 = fmaxf(m0, __shfl_xor_sync(0xffffffffu, m0, 2));
            m1 = fmaxf(m1, __shfl_xor_sync(0xffffffffu, m1, 2));
            m0 *= cs; m1 *= cs;
            float l0 = 0.f, l1 = 0.f;
#pragma unroll
            for (int j = 0; j < 8; j++) {
                s[4 * j]     = ex2(fmaf(s[4 * j], cs, -m0));
                s[4 * j + 1] = ex2(fmaf(s[4 * j + 1], cs, -m0));
                s[4 * j + 2] = ex2(fmaf(s[4 * j + 2], cs, -m1));
                s[4 * j + 3] = ex2(fmaf(s[4 * j + 3], cs, -m1));
                l0 += s[4 * j] + s[4 * j + 1];
                l1 += s[4 * j + 2] + s[4 * j + 3];
            }
            l0 += __shfl_xor_sync(0xffffffffu, l0, 1);
            l1 += __shfl_xor_sync(0xffffffffu, l1, 1);
            l0 += __shfl_xor_sync(0xffffffffu, l0, 2);
            l1 += __shfl_xor_sync(0xffffffffu, l1, 2);
            const float r0 = rcp(l0), r1 = rcp(l1);
#pragma unroll
            for (int j = 0; j < 8; j++) {
                pa[2 * j]     = pack_bf16(s[4 * j] * r0, s[4 * j + 1] * r0);
                pa[2 * j + 1] = pack_bf16(s[4 * j + 2] * r1, s[4 * j + 3] * r1);
            }
        }

        fence_regs(pa);
        if (alone) {
            finish_alone(pa, dX + (((8192u >> 4) - 1) << 16), dWv, tmo.m, st);
            return;
        }
        lnk = baton_wait_pub(st, pa[15], pub);
        if ((st & kFirst) && tid_now() == 0) set_link(1, 10);
        wg_fence();
        Gemm3<3>::run(acc, pa, dX + (((8192u >> 4) - 1) << 16));
        wg_commit();
        asm volatile("{\n.reg .pred p;\nsetp.ge.u32 p, %0, %1;\n@p st.volatile.shared.u8 [%2], %3;\n}\n"
                     ::"r"(pub), "r"(kNWin - kNWG * gridDim.x), "r"(kMarks + (tid_now() >> 7)), "r"(1) : "memory");
        baton_pass(lnk, st);
        const int nxt = (int)(__reduce_or_sync(0xffffffffu, pub) + kNWG * gridDim.x);
        wg_wait0();
        fence_regs(acc);
        fence_regs(pa);

        if (((tid_now() >> 5) & 3) == 0 && nxt < kNWin) {
            asm volatile("bar.sync %0, 128;" ::"r"((tid_now() >> 7) + 1) : "memory");
            if (elect_one()) {
                const uint32_t wgl = tid_now() >> 7;
                const uint32_t bar = sbase + kOffBar + 8 * wgl;
                mbar_expect_tx(bar, kXBytes);
                tma_load_x(sbase + kOffX + wgl * kXBytes, &tmx, bar, nxt);
            }
            __syncwarp();
        } else {
            asm volatile("bar.arrive %0, 128;" ::"r"((tid_now() >> 7) + 1) : "memory");
        }
#pragma unroll
        for (int i = 0; i < 48; i++) fa[i] = pack_bf16(acc[2 * i], acc[2 * i + 1]);

        asm volatile("st.volatile.shared.v4.b32 [%4], {%0, %1, %2, %3};"
                     :: "r"(fa[44]), "r"(fa[45]), "r"(fa[46]), "r"(fa[47]), "r"(sbase + kOffStash + (tid_now() & 127) * 16) : "memory");
        fence_regs(fa);
        if (((tid_now() >> 5) & 3) == 0 && nxt + kPfMin < kNWin) {
            if (elect_one()) {
                const int base = kNWG * (int)gridDim.x, t = nxt - base;
                const int hi = min(nxt + pf_lead(t), kNWin - 1);
                int lo = max(max(nxt - 1 + pf_lead(t - 1), nxt) + 1, base + kPfInit * (int)gridDim.x);
#pragma unroll 1
                for (; lo <= hi; lo++) prefetch_x(&tmp, lo);
            }
            __syncwarp();
        }
        if (nxt >= kNWin) {
            finish_last(fa, dWv, tmo.m, st);
            return;
        }
        lnk = baton_wait(st, fa[43]);
        wg_fence();
        Gemm4<0, 1>::run(acc, fa, dWv);
        wg_commit();
        Gemm4<2, 10>::run(acc, fa, dWv);
        wg_commit();
        wg_wait1();
        uint32_t fl[4];
        asm volatile("ld.volatile.shared.v4.b32 {%0, %1, %2, %3}, [%4];"
                     : "=r"(fl[0]), "=r"(fl[1]), "=r"(fl[2]), "=r"(fl[3]) : "r"(sbase + kOffStash + (tid_now() & 127) * 16) : "memory");
        wg_fence();
        wg192_rs<false, 0, koff(11, 24576)>(acc, fl, dWv);
        wg_commit();
        baton_pass(lnk, st);
        st = ((st ^ kPhase) & (kPhase | kSolo)) | st_win(st) << 4 | nxt << 17;
        uint32_t landed;
        asm volatile("{\n.reg .pred p;\nmbarrier.test_wait.parity.shared::cta.b64 p, [%1], %2;\nselp.b32 %0, 1, 0, p;\n}\n"
                     : "=r"(landed) : "r"(sbase + kOffBar + 8 * (tid_now() >> 7)), "r"(st & kPhase) : "memory");
        wg_wait0();
        fence_regs(acc);
        fence_regs(fa);
        fence_regs(fl);

#pragma unroll
        for (int a = 0; a < 6; a++)
#pragma unroll
            for (int r = 0; r < 2; r++)
                hv[2 * a + r] = make_uint4(pack_bf16(acc[16 * a + 2 * r], acc[16 * a + 2 * r + 1]), pack_bf16(acc[16 * a + 2 * r + 4], acc[16 * a + 2 * r + 5]),
                                           pack_bf16(acc[16 * a + 2 * r + 8], acc[16 * a + 2 * r + 9]), pack_bf16(acc[16 * a + 2 * r + 12], acc[16 * a + 2 * r + 13]));
        if (!landed) mbar_wait(sbase + kOffBar + 8 * (tid_now() >> 7), st & kPhase);
    }
}

typedef CUresult (*EncodeTiledFn)(CUtensorMap*, CUtensorMapDataType, cuuint32_t, void*, const cuuint64_t*,
                                  const cuuint64_t*, const cuuint32_t*, const cuuint32_t*, CUtensorMapInterleave,
                                  CUtensorMapSwizzle, CUtensorMapL2promotion, CUtensorMapFloatOOBfill);

}

extern "C" void kernel_launch(void* const* d_in, const int* in_sizes, int n_in, void* d_out, int out_size) {
    (void)in_sizes; (void)n_in; (void)out_size;
    const __nv_bfloat16* x    = (const __nv_bfloat16*)d_in[0];
    const __nv_bfloat16* wqkv = (const __nv_bfloat16*)d_in[1];
    const __nv_bfloat16* wo   = (const __nv_bfloat16*)d_in[2];

    static EncodeTiledFn encode = nullptr;
    static int num_sms = 0;
    static Scratch* scratch = nullptr;
    if (!encode) {
        void* fn = nullptr;
        cudaDriverEntryPointQueryResult qr;
        cudaGetDriverEntryPoint("cuTensorMapEncodeTiled", &fn, cudaEnableDefault, &qr);
        encode = (EncodeTiledFn)fn;
        cudaGetSymbolAddress((void**)&scratch, g_scratch);
        int dev = 0;
        cudaGetDevice(&dev);
        cudaDeviceGetAttribute(&num_sms, cudaDevAttrMultiProcessorCount, dev);
        cudaFuncSetAttribute(swin_attn_kernel, cudaFuncAttributeMaxDynamicSharedMemorySize, kSmemBytes);
    }
    CUtensorMap tmx;
    const cuuint64_t gdim[4] = {64, (cuuint64_t)kHW, (cuuint64_t)kHW, 3};
    const cuuint64_t gstr[3] = {(cuuint64_t)kC * 2, (cuuint64_t)kHW * kC * 2, 128};
    const cuuint32_t box[4] = {64, 8, 8, 3};
    const cuuint32_t estr[4] = {1, 1, 1, 1};
    encode(&tmx, CU_TENSOR_MAP_DATA_TYPE_BFLOAT16, 4, (void*)x, gdim, gstr, box, estr, CU_TENSOR_MAP_INTERLEAVE_NONE,
           CU_TENSOR_MAP_SWIZZLE_128B, CU_TENSOR_MAP_L2_PROMOTION_NONE, CU_TENSOR_MAP_FLOAT_OOB_FILL_NONE);

    CUtensorMap tmp;
    const cuuint64_t pdim[3] = {(cuuint64_t)kC, (cuuint64_t)kHW, (cuuint64_t)kHW};
    const cuuint64_t pstr[2] = {(cuuint64_t)kC * 2, (cuuint64_t)kHW * kC * 2};
    const cuuint32_t pbox[3] = {(cuuint32_t)kC, 8, 8};
    encode(&tmp, CU_TENSOR_MAP_DATA_TYPE_BFLOAT16, 3, (void*)x, pdim, pstr, pbox, estr, CU_TENSOR_MAP_INTERLEAVE_NONE,
           CU_TENSOR_MAP_SWIZZLE_NONE, CU_TENSOR_MAP_L2_PROMOTION_NONE, CU_TENSOR_MAP_FLOAT_OOB_FILL_NONE);
    CUtensorMap tmc;
    const cuuint32_t boxc[4] = {64, 8, 8, 1};
    encode(&tmc, CU_TENSOR_MAP_DATA_TYPE_BFLOAT16, 4, (void*)x, gdim, gstr, boxc, estr, CU_TENSOR_MAP_INTERLEAVE_NONE,
           CU_TENSOR_MAP_SWIZZLE_128B, CU_TENSOR_MAP_L2_PROMOTION_NONE, CU_TENSOR_MAP_FLOAT_OOB_FILL_NONE);
    OutMaps tmo;
    const cuuint32_t boxo[4] = {64, 8, 1, 2};
    encode(&tmo.m[0], CU_TENSOR_MAP_DATA_TYPE_BFLOAT16, 4, d_out, gdim, gstr, boxo, estr, CU_TENSOR_MAP_INTERLEAVE_NONE,
           CU_TENSOR_MAP_SWIZZLE_128B, CU_TENSOR_MAP_L2_PROMOTION_NONE, CU_TENSOR_MAP_FLOAT_OOB_FILL_NONE);
    const cuuint64_t odim[4] = {64, (cuuint64_t)kHW, (cuuint64_t)kHW, 2};
    const cuuint64_t ostr[3] = {(cuuint64_t)kC * 2, (cuuint64_t)kHW * kC * 2, (cuuint64_t)kHW * kC * 2 - 256};
    encode(&tmo.m[1], CU_TENSOR_MAP_DATA_TYPE_BFLOAT16, 4, (char*)d_out + 256, odim, ostr, boxo, estr, CU_TENSOR_MAP_INTERLEAVE_NONE,
           CU_TENSOR_MAP_SWIZZLE_128B, CU_TENSOR_MAP_L2_PROMOTION_NONE, CU_TENSOR_MAP_FLOAT_OOB_FILL_NONE);
    const cuuint32_t boxs[4] = {64, 8, 2, 1};
    encode(&tmo.m[2], CU_TENSOR_MAP_DATA_TYPE_BFLOAT16, 4, d_out, gdim, gstr, boxs, estr, CU_TENSOR_MAP_INTERLEAVE_NONE,
           CU_TENSOR_MAP_SWIZZLE_128B, CU_TENSOR_MAP_L2_PROMOTION_NONE, CU_TENSOR_MAP_FLOAT_OOB_FILL_NONE);
    swin_attn_kernel<<<num_sms, kThreads, kSmemBytes, cudaStreamPerThread>>>(wqkv, wo, scratch, d_out, tmo, tmx, tmp, tmc);
}
```

```cpp
#include <cuda_runtime.h>
#include <cuda_bf16.h>
#include <cuda.h>
#include <stdint.h>

namespace {

constexpr int kC      = 192;
constexpr int kHW     = 512;
constexpr int kNWin   = 4096;
constexpr int kXBytes = 64 * kC * 2;
constexpr int kWBytes = kC * kC * 2;
constexpr int kNWG    = 3;
constexpr int kThreads = kNWG * 128;
constexpr int kTiles  = 144;
constexpr int kPfInit = 2, kPfUp = 160, kPfPeak = 400, kPfHold = 800, kPfDown1 = 40, kPfBase2 = 300, kPfDown2 = 12, kPfMin = 140;
__device__ __forceinline__ int pf_lead(int t, int G) {
    return min(min(kPfInit * G + ((t * kPfUp) >> 8), kPfPeak),
               max(max(kPfPeak - (((t - kPfHold) * kPfDown1) >> 8), kPfBase2 - ((t * kPfDown2) >> 8)), kPfMin));
}
constexpr int kEvictFrom = 3100;
constexpr int kPaceStart = 100, kPaceSpread = 500, kPaceStep0 = 750, kPaceMid = 2100, kPaceStep = 550;
constexpr uint32_t kMqkHint = 72;
constexpr uint32_t kPollDelay = 200;
constexpr uint32_t kWvoDelay = 1000;

constexpr int kOffWm  = 0;
constexpr int kOffWv  = kWBytes;
constexpr int kOffX   = 2 * kWBytes;
constexpr int kOffStage = kOffX + kNWG * kXBytes;
constexpr int kOffStash = kOffStage + 8192;
constexpr int kOffBar = kOffStash + 2048;
constexpr int kSmemBytes = kOffBar + 256;
constexpr uint32_t kSmemBase = 1024;

struct Scratch {
    uint32_t ticket[32];
    uint32_t epoch[32];
    uint32_t cnt_v[32];
    uint32_t cnt_m[32];
    uint4 img[2][2][kWBytes / 16];
};
__device__ __align__(128) Scratch g_scratch;

__device__ __forceinline__ uint32_t smem_u32(const void* p) { return (uint32_t)__cvta_generic_to_shared(p); }

__device__ __forceinline__ void mbar_init(uint32_t bar, uint32_t count) {
    asm volatile("mbarrier.init.shared::cta.b64 [%0], %1;" ::"r"(bar), "r"(count) : "memory");
}
__device__ __forceinline__ void mbar_expect_tx(uint32_t bar, uint32_t bytes) {
    asm volatile("mbarrier.arrive.expect_tx.shared::cta.b64 _, [%0], %1;" ::"r"(bar), "r"(bytes) : "memory");
}
__device__ __forceinline__ void mbar_wait(uint32_t bar, uint32_t parity) {
    uint32_t ok;
    uint32_t spins = 0;
    do {
        asm volatile("{\n.reg .pred p;\n"
                     "mbarrier.try_wait.parity.shared::cta.b64 p, [%1], %2;\n"
                     "selp.b32 %0, 1, 0, p;\n}\n"
                     : "=r"(ok) : "r"(bar), "r"(parity) : "memory");
        if (++spins > (1u << 26)) __trap();
    } while (!ok);
}
__device__ __forceinline__ uint32_t tid_now() {
    uint32_t t;
    asm volatile("mov.u32 %0, %%tid.x;" : "=r"(t));
    return t;
}
__device__ __forceinline__ bool elect_one() {
    uint32_t pred;
    asm volatile("{\n.reg .pred p;\nelect.sync _|p, 0xffffffff;\nselp.b32 %0, 1, 0, p;\n}\n" : "=r"(pred));
    return pred != 0;
}
__device__ __forceinline__ uint32_t wg_uniform() { return __reduce_or_sync(0xffffffffu, tid_now() >> 7); }
constexpr uint32_t kLink = kSmemBase + kOffBar + 64;
constexpr uint32_t kMarks = kLink + 24;
constexpr uint32_t kPhase = 1;
constexpr uint32_t kSolo = 2;
constexpr uint32_t kFirst = 4;
constexpr uint32_t kRound = 8;
constexpr uint32_t kVeryFirst = 1u << 16;
__device__ __forceinline__ int st_out(uint32_t st) { return (st >> 4) & 0xfff; }
__device__ __forceinline__ int st_win(uint32_t st) { return st >> 17; }
__device__ __forceinline__ uint32_t baton_wait(uint32_t st, uint32_t packed) {
    if (packed == 0xffffffffu) __trap();
    if (!(st & kSolo)) asm volatile("bar.sync %0, 256;" ::"r"((tid_now() >> 7) + 8) : "memory");
    uint32_t lnk;
    asm volatile("ld.volatile.shared.u32 %0, [%1];" : "=r"(lnk) : "r"(kLink + 8 * (tid_now() >> 7)) : "memory");
    return lnk;
}
__device__ __forceinline__ uint32_t baton_wait_pub(uint32_t st, uint32_t packed, uint32_t& pub) {
    if (packed == 0xffffffffu) __trap();
    asm volatile("bar.sync %0, %1;" ::"r"((tid_now() >> 7) + 8), "r"(st & kSolo ? 128 : 256) : "memory");
    uint32_t lnk;
    asm volatile("ld.volatile.shared.v2.u32 {%0, %1}, [%2];" : "=r"(lnk), "=r"(pub) : "r"(kLink + 8 * (tid_now() >> 7)) : "memory");
    return lnk;
}
__device__ __forceinline__ void baton_pass(uint32_t lnk, uint32_t& st) {
    const bool other = lnk != (tid_now() >> 7) + 8;
    if (other) asm volatile("bar.arrive %0, 256;" ::"r"(lnk) : "memory");
    st = other ? st & ~kSolo : st | kSolo;
}
__device__ __forceinline__ void set_link(int w, uint32_t v) { asm volatile("st.volatile.shared.u32 [%0], %1;" ::"r"(kLink + 8 * w), "r"(v) : "memory"); }
constexpr uint64_t kPolNormal = 0x1000000000000000ull, kPolFirst = 0x12F0000000000000ull;
__device__ __forceinline__ void tma_load_x(uint32_t dst, const CUtensorMap* tm, uint32_t bar, int win) {
    const int wh = win >> 6, ww = win & 63;
    asm volatile("cp.async.bulk.tensor.4d.shared::cluster.global.mbarrier::complete_tx::bytes.L2::cache_hint"
                 " [%0], [%1, {%3, %4, %5, %6}], [%2], %7;"
                 ::"r"(dst), "l"(tm), "r"(bar), "r"(0), "r"(ww * 8), "r"(wh * 8), "r"(0), "l"(win >= kEvictFrom ? kPolFirst : kPolNormal) : "memory");
}
__device__ __forceinline__ void tma_load_x_chunk(uint32_t dst, const CUtensorMap* tm, uint32_t bar, int win, int chunk) {
    const int wh = win >> 6, ww = win & 63;
    asm volatile("cp.async.bulk.tensor.4d.shared::cluster.global.mbarrier::complete_tx::bytes"
                 " [%0], [%1, {%3, %4, %5, %6}], [%2];"
                 ::"r"(dst), "l"(tm), "r"(bar), "r"(0), "r"(ww * 8), "r"(wh * 8), "r"(chunk) : "memory");
}
__device__ __forceinline__ void bulk_load(uint32_t dst, const void* src, uint32_t bytes, uint32_t bar) {
    asm volatile("cp.async.bulk.shared::cluster.global.mbarrier::complete_tx::bytes [%0], [%1], %2, [%3];"
                 ::"r"(dst), "l"(src), "r"(bytes), "r"(bar) : "memory");
}

__device__ __forceinline__ void wg_fence()  { asm volatile("wgmma.fence.sync.aligned;" ::: "memory"); }
__device__ __forceinline__ void wg_commit() { asm volatile("wgmma.commit_group.sync.aligned;" ::: "memory"); }
__device__ __forceinline__ void wg_wait0()  { asm volatile("wgmma.wait_group.sync.aligned 0;" ::: "memory"); }
__device__ __forceinline__ void wg_wait1()  { asm volatile("wgmma.wait_group.sync.aligned 1;" ::: "memory"); }
__device__ __forceinline__ void wg_wait2()  { asm volatile("wgmma.wait_group.sync.aligned 2;" ::: "memory"); }

template <int N> __device__ __forceinline__ void fence_regs(float (&d)[N]) {
#pragma unroll
    for (int i = 0; i < N; i++) asm volatile("" : "+f"(d[i])::"memory");
}
template <int N> __device__ __forceinline__ void fence_regs(uint32_t (&d)[N]) {
#pragma unroll
    for (int i = 0; i < N; i++) asm volatile("" : "+r"(d[i])::"memory");
}

#define ACC8(c, d, i) c(d[i]), c(d[i + 1]), c(d[i + 2]), c(d[i + 3]), c(d[i + 4]), c(d[i + 5]), c(d[i + 6]), c(d[i + 7])
#define ACC32(c, d) ACC8(c, d, 0), ACC8(c, d, 8), ACC8(c, d, 16), ACC8(c, d, 24)
#define ACC96(c, d) ACC32(c, d), ACC8(c, d, 32), ACC8(c, d, 40), ACC8(c, d, 48), ACC8(c, d, 56), \
                    ACC8(c, d, 64), ACC8(c, d, 72), ACC8(c, d, 80), ACC8(c, d, 88)
#define C_IO(x) "+f"(x)
#define C_O(x) "=f"(x)
#define REGS32 "{%0, %1, %2, %3, %4, %5, %6, %7, %8, %9, %10, %11, %12, %13, %14, %15, " \
               "%16, %17, %18, %19, %20, %21, %22, %23, %24, %25, %26, %27, %28, %29, %30, %31}"
#define REGS96 "{%0, %1, %2, %3, %4, %5, %6, %7, %8, %9, %10, %11, %12, %13, %14, %15, " \
               "%16, %17, %18, %19, %20, %21, %22, %23, %24, %25, %26, %27, %28, %29, %30, %31, " \
               "%32, %33, %34, %35, %36, %37, %38, %39, %40, %41, %42, %43, %44, %45, %46, %47, " \
               "%48, %49, %50, %51, %52, %53, %54, %55, %56, %57, %58, %59, %60, %61, %62, %63, " \
               "%64, %65, %66, %67, %68, %69, %70, %71, %72, %73, %74, %75, %76, %77, %78, %79, " \
               "%80, %81, %82, %83, %84, %85, %86, %87, %88, %89, %90, %91, %92, %93, %94, %95}"

#define DESC_HI "0x40000040"
#define MK_DESC(name, lo, off) "add.u32 t, " lo ", " off ";\nmov.b64 " name ", {t, " DESC_HI "};\n"

template <bool First, int OA, int OB> __device__ __forceinline__ void wg192_ss(float (&d)[96], uint32_t la, uint32_t lb) {
    if constexpr (First)
        asm volatile("{\n.reg .pred p;\n.reg .b32 t;\n.reg .b64 da, db;\nsetp.ne.b32 p, 0, 0;\n"
                     MK_DESC("da", "%96", "%98") MK_DESC("db", "%97", "%99")
                     "wgmma.mma_async.sync.aligned.m64n192k16.f32.bf16.bf16 " REGS96 ", da, db, p, 1, 1, 0, 0;\n}\n"
                     : ACC96(C_O, d) : "r"(la), "r"(lb), "n"(OA), "n"(OB));
    else
        asm volatile("{\n.reg .pred p;\n.reg .b32 t;\n.reg .b64 da, db;\nsetp.ne.b32 p, 1, 0;\n"
                     MK_DESC("da", "%96", "%98") MK_DESC("db", "%97", "%99")
                     "wgmma.mma_async.sync.aligned.m64n192k16.f32.bf16.bf16 " REGS96 ", da, db, p, 1, 1, 0, 0;\n}\n"
                     : ACC96(C_IO, d) : "r"(la), "r"(lb), "n"(OA), "n"(OB));
}
template <bool First, int TB, int OB> __device__ __forceinline__ void wg192_rs(float (&d)[96], const uint32_t* a, uint32_t lb) {
    if constexpr (First)
        asm volatile("{\n.reg .pred p;\n.reg .b32 t;\n.reg .b64 db;\nsetp.ne.b32 p, 0, 0;\n"
                     MK_DESC("db", "%100", "%102")
                     "wgmma.mma_async.sync.aligned.m64n192k16.f32.bf16.bf16 " REGS96 ", {%96, %97, %98, %99}, db, p, 1, 1, %101;\n}\n"
                     : ACC96(C_O, d) : "r"(a[0]), "r"(a[1]), "r"(a[2]), "r"(a[3]), "r"(lb), "n"(TB), "n"(OB));
    else
        asm volatile("{\n.reg .pred p;\n.reg .b32 t;\n.reg .b64 db;\nsetp.ne.b32 p, 1, 0;\n"
                     MK_DESC("db", "%100", "%102")
                     "wgmma.mma_async.sync.aligned.m64n192k16.f32.bf16.bf16 " REGS96 ", {%96, %97, %98, %99}, db, p, 1, 1, %101;\n}\n"
                     : ACC96(C_IO, d) : "r"(a[0]), "r"(a[1]), "r"(a[2]), "r"(a[3]), "r"(lb), "n"(TB), "n"(OB));
}
template <bool First, int TB, int OB> __device__ __forceinline__ void wg64_rs(float (&d)[32], const uint32_t* a, uint32_t lb) {
    if constexpr (First)
        asm volatile("{\n.reg .pred p;\n.reg .b32 t;\n.reg .b64 db;\nsetp.ne.b32 p, 0, 0;\n"
                     MK_DESC("db", "%36", "%38")
                     "wgmma.mma_async.sync.aligned.m64n64k16.f32.bf16.bf16 " REGS32 ", {%32, %33, %34, %35}, db, p, 1, 1, %37;\n}\n"
                     : ACC32(C_O, d) : "r"(a[0]), "r"(a[1]), "r"(a[2]), "r"(a[3]), "r"(lb), "n"(TB), "n"(OB));
    else
        asm volatile("{\n.reg .pred p;\n.reg .b32 t;\n.reg .b64 db;\nsetp.ne.b32 p, 1, 0;\n"
                     MK_DESC("db", "%36", "%38")
                     "wgmma.mma_async.sync.aligned.m64n64k16.f32.bf16.bf16 " REGS32 ", {%32, %33, %34, %35}, db, p, 1, 1, %37;\n}\n"
                     : ACC32(C_IO, d) : "r"(a[0]), "r"(a[1]), "r"(a[2]), "r"(a[3]), "r"(lb), "n"(TB), "n"(OB));
}
template <int OB> __device__ __forceinline__ void wg64_rs_reuse(float (&d)[32], const uint32_t* a, uint32_t lb, uint32_t one) {
    asm volatile("{\n.reg .pred p;\n.reg .b32 t;\n.reg .b64 db;\nsetp.ne.b32 p, %38, 1;\n"
                 MK_DESC("db", "%36", "%37")
                 "wgmma.mma_async.sync.aligned.m64n64k16.f32.bf16.bf16 " REGS32 ", {%32, %33, %34, %35}, db, p, 1, 1, 0;\n}\n"
                 : ACC32(C_IO, d) : "r"(a[0]), "r"(a[1]), "r"(a[2]), "r"(a[3]), "r"(lb), "n"(OB), "r"(one));
}
__host__ __device__ constexpr int koff(int kk, int chunk) { return ((kk >> 2) * chunk + (kk & 3) * 32) >> 4; }

__device__ __forceinline__ void stsm4(uint32_t addr, const uint4& v) {
    asm volatile("stmatrix.sync.aligned.m8n8.x4.shared.b16 [%0], {%1, %2, %3, %4};" ::"r"(addr), "r"(v.x), "r"(v.y), "r"(v.z), "r"(v.w) : "memory");
}
__device__ __forceinline__ void bulk_wait_read() {
    asm volatile("cp.async.bulk.wait_group.read 0;" ::: "memory");
}
__device__ __forceinline__ uint32_t stage_addr(uint32_t slot, uint32_t l) { return slot + (l & 7) * 128 + ((((l >> 3) & 3) ^ (l & 7)) << 4); }
__device__ __forceinline__ void stage_fence() {
    asm volatile("fence.proxy.async.shared::cta;" ::: "memory");
    __syncwarp();
}
template <int R> __device__ __forceinline__ void store_round(const uint4 (&h)[12], uint32_t slot, const CUtensorMap* tm, int col, int row) {
    const uint32_t sa = stage_addr(slot, tid_now());
#pragma unroll
    for (int i = 0; i < 2; i++) {
        const int r = (2 * R + i) / 3, c = (2 * R + i) % 3;
        stsm4(sa + i * 1024, h[4 * c + r]);
        stsm4((sa ^ 64) + i * 1024, h[4 * c + 2 + r]);
    }
    stage_fence();
    asm volatile("{\n.reg .pred p;\nelect.sync _|p, 0xffffffff;\n"
                 "@p cp.async.bulk.tensor.4d.global.shared::cta.bulk_group [%0, {%2, %3, %4, %5}], [%1];\n"
                 "@p cp.async.bulk.commit_group;\n}\n"
                 ::"l"(tm + (R == 1)), "r"(slot), "r"(0), "r"(col), "r"(row + (R == 2)), "r"((int)(R == 2)) : "memory");
}
__device__ __forceinline__ uint32_t warp4_uniform() { return __reduce_or_sync(0xffffffffu, (tid_now() >> 5) & 3); }
struct OutMaps { CUtensorMap m[3]; };
__host__ __device__ constexpr uint32_t bar_m(int c) { return kSmemBase + kOffBar + 32 + 8 * c; }
__device__ __forceinline__ void m_load(const Scratch* sc, int c, uint32_t par) {
    mbar_expect_tx(bar_m(c), 24576);
    bulk_load(kSmemBase + kOffWm + c * 24576, sc->img[par][0] + c * 1536, 24576, bar_m(c));
}
__device__ __forceinline__ bool m_agree(uint32_t ok) {
    uint32_t all;
    asm volatile("{\n.reg .pred p, q;\nsetp.ne.u32 p, %1, 0;\nbar.red.and.pred q, 7, 256, p;\nselp.b32 %0, 1, 0, q;\n}\n" : "=r"(all) : "r"(ok) : "memory");
    return all != 0;
}
__device__ __forceinline__ void m_check(const Scratch* sc, uint32_t par) {
    for (uint32_t round = 0;; round++) {
        uint32_t m = ~0u;
#pragma unroll 1
        for (int c = 0; c < 3; c++) {
            mbar_wait(bar_m(c), round & 1);
#pragma unroll
            for (int j = 0; j < 6; j++) {
                uint32_t v;
                asm volatile("ld.volatile.shared.b32 %0, [%1];" : "=r"(v)
                             : "r"(kSmemBase + kOffWm + c * 24576 + 4096 * j + (tid_now() & 127) * 32 + (tid_now() & 28)) : "memory");
                m = min(m, v);
            }
        }
        if (m_agree(m)) break;
        asm volatile("bar.sync 7, 256;" ::: "memory");
        if (round > (1u << 20)) __trap();
        if (tid_now() == 128) {
            m_load(sc, 0, par); m_load(sc, 1, par); m_load(sc, 2, par);
        }
    }
}
constexpr uint32_t kBarV = kSmemBase + kOffBar + 56;
__device__ __forceinline__ void v_load(const Scratch* sc, uint32_t par) {
    mbar_expect_tx(kBarV, kWBytes);
#pragma unroll 1
    for (int c = 0; c < 3; c++) bulk_load(kSmemBase + kOffWv + c * 24576, sc->img[par][1] + c * 1536, 24576, kBarV);
}
constexpr uint32_t kScAddr = kSmemBase + kOffBar + 96;
__device__ __forceinline__ void v_check(uint32_t st) {
    for (uint32_t round = 0;; round++) {
        mbar_wait(kBarV, round & 1);
        uint32_t m = ~0u;
#pragma unroll
        for (int j = 0; j < 18; j++) {
            uint32_t v;
            asm volatile("ld.volatile.shared.b32 %0, [%1];" : "=r"(v)
                         : "r"(kSmemBase + kOffWv + 4096 * j + (tid_now() & 127) * 32 + (tid_now() & 28)) : "memory");
            m = min(m, v);
        }
        uint32_t all;
        asm volatile("{\n.reg .pred p, q;\nsetp.ne.u32 p, %1, 0;\nbar.red.and.pred q, 14, 128, p;\nselp.b32 %0, 1, 0, q;\n}\n" : "=r"(all) : "r"(m) : "memory");
        if (all) break;
        if (round > (1u << 20)) __trap();
        if (tid_now() == 0) {
            const Scratch* q;
            asm volatile("ld.volatile.shared.u64 %0, [%1];" : "=l"(q) : "r"(kScAddr) : "memory");
            v_load(q, st_out(st));
        }
    }
}
__host__ __device__ constexpr uint32_t bar_x(int w, int c) { return kSmemBase + kOffBar + 128 + 32 * w + 8 * c; }
template <int K> struct Gemm1 {
    static __device__ __forceinline__ void run(float (&d)[96], uint32_t lx, uint32_t lw, bool very_first, uint32_t st) {
        if constexpr (K > 0) Gemm1<K - 1>::run(d, lx, lw, very_first, st);
        if constexpr (K == 0 || K == 4 || K == 8) {
            if constexpr (K == 0) {
                if (very_first) mbar_wait(bar_m(0), (st & kRound) != 0);
            } else if (st & kFirst) {
                mbar_wait(bar_x(0, K / 4) + 32 * (tid_now() >> 7), 0);
                if (very_first) mbar_wait(bar_m(K / 4), (st & kRound) != 0);
            }
            wg_fence();
        }
        wg192_ss<K == 0, koff(K, 8192), koff(K, 24576)>(d, lx, lw);
    }
};
__device__ __forceinline__ void draw_ticket(uint32_t& ticket) {
    asm volatile("{\n.reg .pred p;\n.reg .b64 a;\nsetp.eq.u32 p, %1, 0;\nld.volatile.shared.u64 a, [%3];\n"
                 "@p atom.relaxed.gpu.global.inc.u32 %0, [a], %2;\n}\n"
                 : "+r"(ticket) : "r"(tid_now() & 127), "n"(kNWin - 1), "r"(kScAddr) : "memory");
}
template <int KK> struct Gemm2 { static __device__ __forceinline__ void run(float (&d)[32], const uint32_t* a, uint32_t lx, uint32_t lnk, uint32_t& st) {
    Gemm2<KK - 1>::run(d, a, lx, lnk, st); wg64_rs<KK == 0, 0, koff(KK, 8192)>(d, a + 4 * KK, lx);
    if constexpr (KK == 9) {
        __syncwarp();
        bulk_wait_read();
        baton_pass(lnk, st);
    } } };
template <> struct Gemm2<-1> { static __device__ __forceinline__ void run(float (&)[32], const uint32_t*, uint32_t, uint32_t, uint32_t&) {} };
template <int KK> struct Gemm3 { static __device__ __forceinline__ void run(float (&d)[96], const uint32_t* a, uint32_t lxt) {
    Gemm3<KK - 1>::run(d, a, lxt); wg192_rs<KK == 0, 1, KK * (2048 >> 4)>(d, a + 4 * KK, lxt); } };
template <> struct Gemm3<-1> { static __device__ __forceinline__ void run(float (&)[96], const uint32_t*, uint32_t) {} };
template <int K0, int KK> struct Gemm4 { static __device__ __forceinline__ void run(float (&d)[96], const uint32_t* a, uint32_t lw) {
    if constexpr (KK > K0) Gemm4<K0, KK - 1>::run(d, a, lw);
    wg192_rs<KK == 0, 0, koff(KK, 24576)>(d, a + 4 * KK, lw); } };

template <int C, int KK> struct Gemm3s { static __device__ __forceinline__ void run(float (&d)[32], const uint32_t* a, uint32_t lxt) {
    if constexpr (KK > 0) Gemm3s<C, KK - 1>::run(d, a, lxt);
    wg64_rs<KK == 0, 1, (C * 8192 + KK * 2048) / 16>(d, a + 4 * KK, lxt); } };
template <int C, int K0, int KK> struct Gemm4s { static __device__ __forceinline__ void run(float (&d)[32], const uint32_t* a, uint32_t lw, uint32_t one) {
    if constexpr (KK > K0) Gemm4s<C, K0, KK - 1>::run(d, a, lw, one);
    if constexpr (KK == 0) wg64_rs_reuse<C * 8192 / 16>(d, a, lw, one);
    else wg64_rs<false, 0, koff(KK, 24576) + C * 8192 / 16>(d, a + 4 * KK, lw); } };

__device__ __forceinline__ uint32_t pack_bf16(float lo, float hi) {
    uint32_t r;
    asm("cvt.rn.bf16x2.f32 %0, %1, %2;" : "=r"(r) : "f"(hi), "f"(lo));
    return r;
}
__device__ __forceinline__ float ex2(float x) {
    float r;
    asm("ex2.approx.ftz.f32 %0, %1;" : "=f"(r) : "f"(x));
    return r;
}
__device__ __forceinline__ float rcp(float x) {
    float r;
    asm("rcp.approx.ftz.f32 %0, %1;" : "=f"(r) : "f"(x));
    return r;
}
__device__ __forceinline__ void mma16816(float (&c)[4], uint32_t a0, uint32_t a1, uint32_t a2, uint32_t a3,
                                         uint32_t b0, uint32_t b1) {
    asm volatile("mma.sync.aligned.m16n8k16.row.col.f32.bf16.bf16.f32 {%0,%1,%2,%3}, {%4,%5,%6,%7}, {%8,%9}, {%0,%1,%2,%3};"
                 : "+f"(c[0]), "+f"(c[1]), "+f"(c[2]), "+f"(c[3])
                 : "r"(a0), "r"(a1), "r"(a2), "r"(a3), "r"(b0), "r"(b1));
}

struct FoldRegs { uint4 B0[6], B1[6]; uint32_t A[48]; };

__device__ __forceinline__ void st_relaxed64(void* p, uint32_t a, uint32_t b, uint32_t on) {
    asm volatile("{\n.reg .pred q;\nsetp.ne.u32 q, %3, 0;\n@q st.relaxed.gpu.global.v2.b32 [%0], {%1, %2};\n}\n" ::"l"(p), "r"(a), "r"(b), "r"(on) : "memory");
}
__device__ __forceinline__ uint32_t pack_nonzero(float lo, float hi) { const uint32_t v = pack_bf16(lo, hi); return v != 0 ? v : 0x80000000u; }
__device__ __forceinline__ void fold_store(char* img, uint32_t* cnt, uint32_t epoch, uint32_t on, uint32_t zero, int n_lo, int n_hi, int k0, int lane, const float (&c0)[4], const float (&c1)[4]) {
    const int q = lane & 3;
    const int u = ((k0 & 63) >> 3) + (q >> 1);
    const int base = (k0 >> 6) * 24576 + (q & 1) * 8;
    char* p_lo = img + (base + n_lo * 128 + ((u ^ (n_lo & 7)) << 4));
    char* p_hi = img + (base + n_hi * 128 + ((u ^ (n_hi & 7)) << 4));
    const uint32_t v0 = pack_nonzero(c0[0], c0[1]);
    const uint32_t par = (epoch & 1) | (v0 & zero);
    st_relaxed64(p_lo + par * (2 * kWBytes), v0, pack_nonzero(c1[0], c1[1]), on);
    st_relaxed64(p_hi + par * (2 * kWBytes), pack_nonzero(c0[2], c0[3]), pack_nonzero(c1[2], c1[3]), on);
    asm volatile("{\n.reg .pred q;\nsetp.ne.u32 q, %1, 0;\n@q red.relaxed.gpu.global.inc.u32 [%0], 0xffff;\n}\n" ::"l"(cnt), "r"(lane == 0 ? on : 0u) : "memory");
    st_relaxed64(p_lo + (par ^ 1) * (2 * kWBytes), 0, 0, on);
    st_relaxed64(p_hi + (par ^ 1) * (2 * kWBytes), 0, 0, on);
}
__device__ __forceinline__ void fold_load_qk(FoldRegs& r, const __nv_bfloat16* __restrict__ wqkv, int tile, int lane) {
    const int g = lane >> 2, q = lane & 3;
    const uint32_t tn = (uint32_t)tile * 171 >> 11, tk = tile - 12 * tn;
    uint32_t oa = tn * (16 * 1152) + (g * 1152 + 16 * q), ob = tk * (16 * 1152) + ((4 * (g >> 1) + (g & 1)) * 1152 + 16 * q);
    asm("" : "+r"(oa), "+r"(ob));
    const uint4* pa0 = reinterpret_cast<const uint4*>(reinterpret_cast<const char*>(wqkv) + oa) + 24;
    const uint4* pa1 = pa0 + 8 * 72;
    const uint4* pb0 = reinterpret_cast<const uint4*>(reinterpret_cast<const char*>(wqkv) + ob);
    const uint4* pb1 = pb0 + 2 * 72;
#pragma unroll
    for (int j = 0; j < 6; j++) {
        const uint4 lo = __ldg(pa0 + 4 * j), hi = __ldg(pa1 + 4 * j);
        r.A[8 * j + 0] = lo.x; r.A[8 * j + 1] = hi.x; r.A[8 * j + 2] = lo.y; r.A[8 * j + 3] = hi.y;
        r.A[8 * j + 4] = lo.z; r.A[8 * j + 5] = hi.z; r.A[8 * j + 6] = lo.w; r.A[8 * j + 7] = hi.w;
        r.B0[j] = __ldg(pb0 + 4 * j);
        r.B1[j] = __ldg(pb1 + 4 * j);
    }
}
__device__ __forceinline__ void fold_load_vo(FoldRegs& r, const __nv_bfloat16* __restrict__ wqkv, const __nv_bfloat16* __restrict__ wo,
                                             int tile, int lane) {
    const int g = lane >> 2, q = lane & 3;
    const int ch0 = (tile / 12) * 16 + 2 * g;
    const int k0 = (tile % 12) * 16;
    const int kb = k0 + 4 * (g >> 1) + (g & 1);
    const uint4* pb0 = reinterpret_cast<const uint4*>(wqkv + (size_t)kb * 576 + 384 + 8 * q);
    const uint4* pb1 = reinterpret_cast<const uint4*>(wqkv + (size_t)(kb + 2) * 576 + 384 + 8 * q);
    const uint32_t* pw = reinterpret_cast<const uint32_t*>(wo + (size_t)(8 * q) * kC + ch0);
#pragma unroll
    for (int j = 0; j < 6; j++) {
        r.B0[j] = __ldg(pb0 + 4 * j);
        r.B1[j] = __ldg(pb1 + 4 * j);
#pragma unroll
        for (int i = 0; i < 8; i++) r.A[8 * j + i] = __ldg(pw + (32 * j + i) * (kC / 2));
    }
}
template <bool kVO>
__device__ __forceinline__ void fold_compute_store(FoldRegs& r, Scratch* sc, int tile, int lane, uint32_t epoch, uint32_t on, uint32_t zero) {
    const int g = lane >> 2;
    float c0[4] = {0.f, 0.f, 0.f, 0.f}, c1[4] = {0.f, 0.f, 0.f, 0.f}, c2[4] = {0.f, 0.f, 0.f, 0.f}, c3[4] = {0.f, 0.f, 0.f, 0.f};
#pragma unroll
    for (int j = 0; j < 6; j++) {
        uint32_t a[8];
        if constexpr (kVO) {
#pragma unroll
            for (int i = 0; i < 4; i++) {
                a[2 * i]     = __byte_perm(r.A[8 * j + 2 * i], r.A[8 * j + 2 * i + 1], 0x5410);
                a[2 * i + 1] = __byte_perm(r.A[8 * j + 2 * i], r.A[8 * j + 2 * i + 1], 0x7632);
            }
        } else {
#pragma unroll
            for (int i = 0; i < 8; i++) asm volatile("prmt.b32 %0, %1, 0, 0x3210;" : "=r"(a[i]) : "r"(r.A[8 * j + i]));
        }
        mma16816(c0, a[0], a[1], a[2], a[3], r.B0[j].x, r.B0[j].y);
        mma16816(c1, a[0], a[1], a[2], a[3], r.B1[j].x, r.B1[j].y);
        mma16816(c2, a[4], a[5], a[6], a[7], r.B0[j].z, r.B0[j].w);
        mma16816(c3, a[4], a[5], a[6], a[7], r.B1[j].z, r.B1[j].w);
    }
#pragma unroll
    for (int i = 0; i < 4; i++) { c0[i] += c2[i]; c1[i] += c3[i]; }
    const int k0 = (tile % 12) * 16;
    if constexpr (kVO) {
        const int n = (tile / 12) * 16 + 2 * g;
        fold_store(reinterpret_cast<char*>(sc->img[0][1]), sc->cnt_v, epoch, on, zero, n, n + 1, k0, lane, c0, c1);
    } else {
        const int n0 = (tile / 12) * 16;
        fold_store(reinterpret_cast<char*>(sc->img[0][0]), sc->cnt_m, epoch, on, zero, n0 + g, n0 + g + 8, k0, lane, c0, c1);
    }
}

__device__ __forceinline__ void prefetch_x(const CUtensorMap* tm, int win) {
    const int wh = win >> 6, ww = win & 63;
    asm volatile("cp.async.bulk.prefetch.tensor.3d.L2.global.tile [%0, {%1, %2, %3}];"
                 ::"l"(tm), "r"(0), "r"(ww * 8), "r"(wh * 8) : "memory");
}

__device__ __forceinline__ void publish(uint32_t ticket) {
    asm volatile("{\n.reg .pred p;\nsetp.eq.u32 p, %2, 0;\n@p st.volatile.shared.u32 [%0], %1;\n}\n"
                 ::"r"(kLink + 4 + 8 * (tid_now() >> 7)), "r"(ticket), "r"(tid_now() & 127) : "memory");
}
__device__ __forceinline__ void reset_for_next_launch() {
    Scratch* q;
    asm volatile("ld.volatile.shared.u64 %0, [%1];" : "=l"(q) : "r"(kScAddr) : "memory");
    q->cnt_v[0] = 0; q->cnt_m[0] = 0; atomicAdd(q->epoch, 1);
}

__device__ __forceinline__ void send_slice(const CUtensorMap* tm, uint32_t slot, uint32_t col, uint32_t row, uint32_t c) {
    stage_fence();
    asm volatile("{\n.reg .pred p;\nelect.sync _|p, 0xffffffff;\n"
                 "@p cp.async.bulk.tensor.4d.global.shared::cta.bulk_group [%0, {%2, %3, %4, %5}], [%1];\n}\n"
                 ::"l"(tm + 2), "r"(slot + c * 2048), "r"(0), "r"(col), "r"(row), "r"(c) : "memory");
}
__device__ __forceinline__ void bulk_commit() { asm volatile("cp.async.bulk.commit_group;" ::: "memory"); }
template <bool AddNz> __device__ __forceinline__ void pack_slice(uint4 (&h)[4], float (&o)[32], float nz) {
    fence_regs(o);
    auto pk = [&](int i) { return pack_bf16(o[i], AddNz ? o[i + 1] + nz : o[i + 1]); };
#pragma unroll
    for (int i = 0; i < 4; i++) {
        const int b = 16 * (i & 1) + 2 * (i >> 1);
        h[i] = make_uint4(pk(b), pk(b + 4), pk(b + 8), pk(b + 12));
    }
#pragma unroll
    for (int i = 0; i < 4; i++) asm volatile("" : "+r"(h[i].x), "+r"(h[i].y), "+r"(h[i].z), "+r"(h[i].w)::"memory");
}
__device__ __forceinline__ void stage_part(uint32_t sa, int c, const uint4 (&h)[4], int i) { stsm4((sa ^ (i & 1) * 64) + (i >> 1) * 1024 + c * 2048, h[i]); }
#define W(C, K0, K1, O) Gemm4s<C, K0, K1>::run(O, fa, dWv, one)
#define W_STAGE(C, O) stage_part(sa, C - 1, h, 0); W(C, 5, 5, O); stage_part(sa, C - 1, h, 1); W(C, 6, 6, O); \
                      stage_part(sa, C - 1, h, 2); W(C, 7, 7, O); stage_part(sa, C - 1, h, 3); W(C, 8, 8, O)

__device__ __forceinline__ void finish_alone(const uint32_t (&pa_in)[16], uint32_t dXt, uint32_t dWv, const CUtensorMap* tm, uint32_t st) {
    uint32_t pa[16];
#pragma unroll
    for (int j = 0; j < 16; j++) pa[j] = pa_in[j];
    char* out;
    asm volatile("ld.volatile.shared.u64 %0, [%1];" : "=l"(out) : "r"(kScAddr + 8) : "memory");
    const uint32_t one = gridDim.y;
    const float nz = __uint_as_float(one << 31);
    float u0[32], u1[32], u2[32];
    float (&o0)[32] = u0, (&o1)[32] = u2, (&o2)[32] = u0;
    uint32_t fa[48];
    uint4 h[4];
    auto pack_a = [&](float (&u)[32], int c) {
        fence_regs(u);
#pragma unroll
        for (int i = 0; i < 16; i++) {
            fa[16 * c + i] = pack_bf16(c != 1 ? u[2 * i] + nz : u[2 * i], u[2 * i + 1]);
            asm volatile("" : "+r"(fa[16 * c + i])::"memory");
        }
        wg_fence();
    };
    const uint32_t t = tid_now(), win = st_win(st);
    const uint32_t slot = kSmemBase + kOffX + (t >> 5) * 6144, sa = stage_addr(slot, t);
    const uint32_t col = (win & 63) * 8, row = (win >> 6) * 8 + ((t >> 4) & 6);
    if (!(st & kSolo)) asm volatile("bar.sync %0, 256;" ::"r"((t >> 7) + 8) : "memory");
    wg_fence();
    Gemm3s<0, 3>::run(u0, pa, dXt); wg_commit();
    Gemm3s<1, 3>::run(u1, pa, dXt); wg_commit();
    Gemm3s<2, 3>::run(u2, pa, dXt); wg_commit();
    wg_wait2(); pack_a(u0, 0);
    W(0, 0, 3, o0); wg_commit();
    wg_wait2(); pack_a(u1, 1);
    W(0, 4, 7, o0); wg_commit();
    wg_wait2(); pack_a(u2, 2);
    W(0, 8, 11, o0); wg_commit();
    W(1, 0, 0, o1);
    asm volatile("bar.sync %0, 128;" ::"r"((t >> 7) + 1) : "memory");
    wg_fence();
    W(1, 1, 4, o1); wg_commit();
    wg_wait1(); pack_slice<true>(h, o0, nz);
    W_STAGE(1, o1);
    W(1, 9, 10, o1);
    send_slice(tm, slot, col, row, 0);
    wg_fence();
    W(1, 11, 11, o1); wg_commit();
    W(2, 0, 4, o2); wg_commit();
    wg_wait1(); pack_slice<false>(h, o1, nz);
    W_STAGE(2, o2);
    W(2, 9, 10, o2);
    send_slice(tm, slot, col, row, 1);
    wg_fence();
    W(2, 11, 11, o2); wg_commit();
    __syncwarp();
    bulk_commit();
    __syncwarp();
    wg_wait0(); pack_slice<false>(h, o2, nz);
    fence_regs(fa);
#pragma unroll
    for (int i = 0; i < 4; i++) stage_part(sa, 2, h, i);
    __syncwarp();
    const uint32_t tok = (t >> 3) & 3, j = t & 7, la = slot + tok * 128 + ((j ^ tok) << 4);
    out += (row * kHW + col + tok) * (kC * 2) + j * 16 + 256;
#pragma unroll
    for (int i = 0; i < 4; i++)
        asm volatile("ld.volatile.shared.v4.b32 {%0, %1, %2, %3}, [%4];" : "=r"(h[i].x), "=r"(h[i].y), "=r"(h[i].z), "=r"(h[i].w)
                     : "r"((la ^ (i & 1) * 64) + i * 512 + 4096) : "memory");
#pragma unroll
    for (int i = 0; i < 4; i++)
        asm volatile("st.global.v4.b32 [%0], {%1, %2, %3, %4};"
                     ::"l"(out + ((i >> 1) * kHW + 4 * (i & 1)) * (kC * 2)), "r"(h[i].x), "r"(h[i].y), "r"(h[i].z), "r"(h[i].w) : "memory");
    __syncwarp();
    bulk_wait_read();
}

__device__ __forceinline__ void finish_last(const uint32_t (&fa_in)[48], uint32_t dWv, const CUtensorMap* tm, uint32_t st) {
    uint32_t fa[48];
#pragma unroll
    for (int j = 0; j < 48; j++) fa[j] = fa_in[j];
    const uint32_t one = gridDim.y;
    const float nz = __uint_as_float(one << 31);
    float o0[32], o1[32];
    float (&o2)[32] = o0;
    uint4 h[4];
    const uint32_t t = tid_now(), win = st_win(st);
    const uint32_t slot = kSmemBase + kOffX + (t >> 5) * 6144, sa = stage_addr(slot, t);
    const uint32_t col = (win & 63) * 8, row = (win >> 6) * 8 + ((t >> 4) & 6);
    const uint32_t la = kLink + 8 * min(t & 127, 2u), me = (t >> 7) + 8;
    uint32_t pub, l;
    const uint32_t lnk = baton_wait_pub(st, sa + la + col + row, pub);
    asm volatile("ld.volatile.shared.u32 %0, [%1];" : "=r"(l) : "r"(la) : "memory");
    wg_fence();
    wg64_rs<true, 0, 0>(o0, fa, dWv);
    W(0, 1, 3, o0);
    asm volatile("{\n.reg .pred p;\nsetp.eq.u32 p, %0, %1;\n@p st.volatile.shared.u32 [%2], %3;\n}\n" ::"r"(l), "r"(me), "r"(la), "r"(lnk) : "memory");
    W(0, 4, 11, o0); wg_commit();
    wg64_rs<true, 0, 8192 / 16>(o1, fa, dWv);
    W(1, 1, 4, o1); wg_commit();
    wg_wait1(); pack_slice<false>(h, o0, nz);
    W_STAGE(1, o1);
    W(1, 9, 10, o1);
    send_slice(tm, slot, col, row, 0);
    wg_fence();
    W(1, 11, 11, o1); wg_commit();
    W(2, 0, 4, o2); wg_commit();
    wg_wait1(); pack_slice<false>(h, o1, nz);
    W_STAGE(2, o2);
    W(2, 9, 9, o2);
    asm volatile("{\n.reg .pred p;\nsetp.ne.u32 p, %0, %1;\n@p bar.arrive %0, 256;\n}\n" ::"r"(lnk), "r"(me) : "memory");
    wg_fence();
    W(2, 10, 11, o2); wg_commit();
    send_slice(tm, slot, col, row, 1);
    wg_wait0(); pack_slice<true>(h, o2, nz);
    fence_regs(fa);
#pragma unroll
    for (int i = 0; i < 4; i++) stage_part(sa, 2, h, i);
    send_slice(tm, slot, col, row, 2);
    bulk_commit();
    bulk_wait_read();
}
#undef W
#undef W_STAGE

__global__ void __launch_bounds__(kThreads, 1)
swin_attn_kernel(const __nv_bfloat16* __restrict__ wqkv, const __nv_bfloat16* __restrict__ wo, Scratch* __restrict__ sc, void* out, const int G,
                 const __grid_constant__ OutMaps tmo, const __grid_constant__ CUtensorMap tmx, const __grid_constant__ CUtensorMap tmp, const __grid_constant__ CUtensorMap tmc) {
    extern __shared__ uint8_t smem_raw[];
    constexpr uint32_t sbase = kSmemBase;
    const int tid = threadIdx.x, lane = tid & 31;

    FoldRegs fq;
#pragma unroll
    for (int j = 0; j < 6; j++) {
        asm volatile("" : "=r"(fq.B0[j].x), "=r"(fq.B0[j].y), "=r"(fq.B0[j].z), "=r"(fq.B0[j].w));
        asm volatile("" : "=r"(fq.B1[j].x), "=r"(fq.B1[j].y), "=r"(fq.B1[j].z), "=r"(fq.B1[j].w));
    }
#pragma unroll
    for (int j = 0; j < 48; j++) asm volatile("" : "=r"(fq.A[j]));
    {
        const int t = blockIdx.x + (tid & 32 ? G : 0);
        if (tid < 64 && t < kTiles) fold_load_qk(fq, wqkv, t, lane);
    }
    __syncwarp();
    uint32_t epoch;
    asm volatile("ld.relaxed.gpu.global.u32 %0, [%1];" : "=r"(epoch)
                 : "l"(reinterpret_cast<const char*>(sc->epoch) + (smem_u32(smem_raw) - kSmemBase)) : "memory");
    if (smem_u32(smem_raw) != kSmemBase) __trap();
    const uint32_t warpu = __reduce_or_sync(0xffffffffu, (uint32_t)tid >> 5), wgu = warpu >> 2;
    const int warp = (int)warpu, wg = (int)wgu;
    const int ftile = blockIdx.x + (warp & 1) * G;
    if (warp == 3) {
        const uint32_t i = blockIdx.x + G * (lane & 15);
        const char* p = lane < 16 ? (const char*)wo + i * 128 : (const char*)wqkv + i * 128 + (i / 3 + 1) * 768;
        if (i < 576) asm volatile("prefetch.global.L2 [%0];" ::"l"(p) : "memory");
    }
    if (warp == 10) {
        if (lane == 0) {
#pragma unroll
            for (int w = 0; w < kNWG; w++) {
                mbar_init(sbase + kOffBar + 8 * w, 1);
#pragma unroll
                for (int c = 0; c < 3; c++) mbar_init(bar_x(w, c), 1);
            }
            asm volatile("fence.mbarrier_init.release.cluster;" ::: "memory");
        }
        __syncwarp();
        asm volatile("bar.arrive 11, 384;" ::: "memory");
        if (lane == 0) {
            const uint32_t t0 = (uint32_t)clock64() + kPaceStart + ((blockIdx.x * 37) & 63) * kPaceSpread / 64;
#pragma unroll 1
            for (int i = 0; i <= 3 * kNWG; i++) {
                while ((int)((uint32_t)clock64() - t0) < (i < 3 ? i * kPaceStep0 : kPaceMid + (i - 3) * kPaceStep)) {}
                const int w = i / 3, c = i % 3;
                if (w < kNWG) {
                    mbar_expect_tx(bar_x(w, c), 8192);
                    tma_load_x_chunk(sbase + kOffX + w * kXBytes + c * 8192, &tmc, bar_x(w, c), w * G + blockIdx.x, c);
                } else {
                    prefetch_x(&tmp, kNWG * G + blockIdx.x);
                }
            }
        }
    }
    if (warp < 3) {
        for (int t = ftile;;) {
            const bool on = warp < 2 && t < kTiles;
            fold_compute_store<false>(fq, sc, t, lane, epoch, on, G >> 16);
            t += 2 * G;
            if (__builtin_expect(warp == 2 || t >= kTiles, 1)) break;
            fold_load_qk(fq, wqkv, t, lane);
        }
    }
    if (warp < 4) {
        asm volatile("bar.sync 11, 384;" ::: "memory");
    } else if (warp == 4) {
        if (lane == 0) {
            asm volatile("st.shared.v4.u32 [%0], {9, 0, 8, 0};\nst.shared.v4.u32 [%0 + 16], {8, 0, 0, 0};" ::"r"(kLink) : "memory");
            asm volatile("st.shared.v2.u64 [%0], {%1, %2};" ::"r"(kScAddr), "l"(sc), "l"(out) : "memory");
            mbar_init(bar_m(0), 1);
            mbar_init(bar_m(1), 1);
            mbar_init(bar_m(2), 1);
            asm volatile("fence.mbarrier_init.release.cluster;" ::: "memory");
        }
        __syncwarp();
        asm volatile("bar.arrive 12, 128;" ::: "memory");
        uint32_t v;
        asm volatile("ld.relaxed.gpu.global.u32 %0, [%1];" : "=r"(v) : "l"(sc->cnt_m) : "memory");
        asm volatile("bar.sync 11, 384;" ::: "memory");
        { const uint32_t t0 = (uint32_t)clock64(); while ((uint32_t)clock64() - t0 < kPollDelay) {} }
        if (lane == 0) {
            uint32_t spins = 0;
            while (v < kMqkHint) {
                asm volatile("ld.relaxed.gpu.global.u32 %0, [%1];" : "=r"(v) : "l"(sc->cnt_m) : "memory");
                if (++spins > (1u << 22)) __trap();
            }
            const uint32_t par = epoch & 1;
            m_load(sc, 0, par); m_load(sc, 1, par); m_load(sc, 2, par);
        }
    } else if (warp == 11) {
        if (lane == 0) {
            mbar_init(kBarV, 1);
            asm volatile("fence.mbarrier_init.release.cluster;" ::: "memory");
        }
        __syncwarp();
        asm volatile("bar.sync 11, 384;" ::: "memory");
        if (lane == 0) {
            uint32_t v, spins = 0;
            do {
                asm volatile("ld.relaxed.gpu.global.u32 %0, [%1];" : "=r"(v) : "l"(sc->cnt_v) : "memory");
                if (++spins > (1u << 22)) __trap();
            } while (v < kTiles);
            uint32_t ok = 0, n = 0;
            while (!ok && ++n < 64)
                asm volatile("{\n.reg .pred p;\nmbarrier.try_wait.parity.shared::cta.b64 p, [%1], 0;\nselp.b32 %0, 1, 0, p;\n}\n" : "=r"(ok) : "r"(bar_m(2)) : "memory");
            v_load(sc, epoch & 1);
        }
    } else if (warp == 10) {
    } else if (warp >= 8) {
        asm volatile("bar.arrive 11, 384;" ::: "memory");
        if (warp == 9) { const uint32_t t0 = (uint32_t)clock64(); while ((uint32_t)clock64() - t0 < kWvoDelay) {} }
        FoldRegs fr;
        for (int t = G - 1 - blockIdx.x + (warp & 1) * G; t < kTiles; t += 2 * G) {
            fold_load_vo(fr, wqkv, wo, t, lane);
            fold_compute_store<true>(fr, sc, t, lane, epoch, 1, G >> 16);
        }
    } else {
        asm volatile("bar.arrive 11, 384;" ::: "memory");
        if (lane == 0) asm volatile("prefetch.tensormap [%0];" ::"l"(warp == 5 ? &tmo.m[0] : warp == 6 ? &tmo.m[1] : &tmx) : "memory");
        if (lane == 0 && warp == 5) asm volatile("prefetch.tensormap [%0];" ::"l"(&tmo.m[2]) : "memory");
        asm volatile("bar.sync 12, 128;" ::: "memory");
    }
    __syncwarp();
    if (wg == 1) m_check(sc, epoch & 1);
    uint4 hv[12];
#pragma unroll
    for (int a = 0; a < 12; a++) asm volatile("" : "=r"(hv[a].x), "=r"(hv[a].y), "=r"(hv[a].z), "=r"(hv[a].w));

    constexpr uint32_t dWm = ((sbase + kOffWm) >> 4) | (1u << 16);
    constexpr uint32_t dWv = ((sbase + kOffWv) >> 4) | (1u << 16);
    const float cs = 0.07216878364870322f * 1.4426950408889634f;
    if (wg == 2) asm volatile("bar.sync 13, 128;" ::: "memory");
    mbar_wait(bar_x(wg, 0), 0);

    uint32_t st = (uint32_t)(wg * G + blockIdx.x) << 17 | kFirst | kPhase | (wg == 0 ? kSolo | kVeryFirst | (epoch & 1) << 4 : 0);

    while (true) {
        float acc[96];
        uint32_t fa[48];
        const uint32_t dX = ((sbase + kOffX + wg_uniform() * kXBytes) >> 4) | (1u << 16);
        uint32_t ticket = 0;
        uint32_t lnk = baton_wait(st, 0);
        while (true) {
            const bool very_first = st & kVeryFirst;
            Gemm1<11>::run(acc, dX, dWm, very_first, st);
            wg_commit();
            if (!very_first) { baton_pass(lnk, st); break; }
            __syncwarp();
            if (m_agree(1)) break;
            wg_wait0();
            asm volatile("bar.arrive 7, 256;" ::: "memory");
            st ^= kRound;
        }
        draw_ticket(ticket);
        if (!(st & kFirst)) {
            const uint32_t w4 = warp4_uniform();
            const uint32_t slot = sbase + kOffStage + w4 * 2048;
            const int col = (st_out(st) & 63) * 8, row = (st_out(st) >> 6) * 8 + 2 * w4;
            store_round<0>(hv, slot, tmo.m, col, row);
            bulk_wait_read();
            __syncwarp();
            store_round<1>(hv, slot, tmo.m, col, row);
            bulk_wait_read();
            __syncwarp();
            store_round<2>(hv, slot, tmo.m, col, row);
        }
        static_assert(kPfInit == 2, "one start-up prefetch in the prologue, one here");
        if ((st & kFirst) && tid_now() == 128) prefetch_x(&tmp, (kNWG + (tid_now() >> 7)) * G + blockIdx.x);
        __syncwarp();
        wg_wait0();
        fence_regs(acc);
#pragma unroll
        for (int i = 0; i < 48; i++) fa[i] = pack_bf16(acc[2 * i], acc[2 * i + 1]);

        float s[32];
        fence_regs(fa);
        if (!(st & kFirst)) publish(ticket);
        uint32_t pub, marks;
        lnk = baton_wait_pub(st, fa[47], pub);
        asm volatile("ld.volatile.shared.u32 %0, [%1];" : "=r"(marks) : "r"(kMarks) : "memory");
        wg_fence();
        Gemm2<11>::run(s, fa, dX, lnk, st);
        wg_commit();
        uint32_t mine = pub;
        if (st & kFirst) {
            publish(ticket);
            mine = ticket;
        }
        if (mine == kNWin - 1 && (tid_now() & 127) == 0) reset_for_next_launch();
        __syncwarp();
        const uint32_t alone = __reduce_or_sync(0xffffffffu, pub >= (uint32_t)(kNWin - kNWG * G) && ((marks | 1u << 8 * (tid_now() >> 7)) ^ (st & kFirst)) == 0x10101);
        wg_wait0();
        fence_regs(s);
        fence_regs(fa);

        uint32_t pa[16];
        {
            float a0[8], a1[8];
#pragma unroll
            for (int j = 0; j < 8; j++) { a0[j] = fmaxf(s[4 * j], s[4 * j + 1]); a1[j] = fmaxf(s[4 * j + 2], s[4 * j + 3]); }
#pragma unroll
            for (int d = 4; d > 0; d >>= 1)
#pragma unroll
                for (int j = 0; j < d; j++) { a0[j] = fmaxf(a0[j], a0[j + d]); a1[j] = fmaxf(a1[j], a1[j + d]); }
            float m0 = a0[0], m1 = a1[0];
            m0 = fmaxf(m0, __shfl_xor_sync(0xffffffffu, m0, 1));
            m1 = fmaxf(m1, __shfl_xor_sync(0xffffffffu, m1, 1));
            m0 = fmaxf(m0, __shfl_xor_sync(0xffffffffu, m0, 2));
            m1 = fmaxf(m1, __shfl_xor_sync(0xffffffffu, m1, 2));
            m0 *= cs; m1 *= cs;
            float l0 = 0.f, l1 = 0.f;
#pragma unroll
            for (int j = 0; j < 8; j++) {
                s[4 * j]     = ex2(fmaf(s[4 * j], cs, -m0));
                s[4 * j + 1] = ex2(fmaf(s[4 * j + 1], cs, -m0));
                s[4 * j + 2] = ex2(fmaf(s[4 * j + 2], cs, -m1));
                s[4 * j + 3] = ex2(fmaf(s[4 * j + 3], cs, -m1));
                l0 += s[4 * j] + s[4 * j + 1];
                l1 += s[4 * j + 2] + s[4 * j + 3];
            }
            l0 += __shfl_xor_sync(0xffffffffu, l0, 1);
            l1 += __shfl_xor_sync(0xffffffffu, l1, 1);
            l0 += __shfl_xor_sync(0xffffffffu, l0, 2);
            l1 += __shfl_xor_sync(0xffffffffu, l1, 2);
            const float r0 = rcp(l0), r1 = rcp(l1);
#pragma unroll
            for (int j = 0; j < 8; j++) {
                pa[2 * j]     = pack_bf16(s[4 * j] * r0, s[4 * j + 1] * r0);
                pa[2 * j + 1] = pack_bf16(s[4 * j + 2] * r1, s[4 * j + 3] * r1);
            }
        }

        fence_regs(pa);
        if (alone) {
            finish_alone(pa, dX + (((8192u >> 4) - 1) << 16), dWv, tmo.m, st);
            return;
        }
        lnk = baton_wait_pub(st, pa[15], pub);
        if ((st & kFirst) && tid_now() == 0) set_link(1, 10);
        wg_fence();
        Gemm3<3>::run(acc, pa, dX + (((8192u >> 4) - 1) << 16));
        wg_commit();
        asm volatile("{\n.reg .pred p;\nsetp.ge.u32 p, %0, %1;\n@p st.volatile.shared.u8 [%2], %3;\n}\n"
                     ::"r"(pub), "r"(kNWin - kNWG * G), "r"(kMarks + (tid_now() >> 7)), "r"(1) : "memory");
        baton_pass(lnk, st);
        const int nxt = (int)(__reduce_or_sync(0xffffffffu, pub) + kNWG * G);
        wg_wait0();
        fence_regs(acc);
        fence_regs(pa);

        if (((tid_now() >> 5) & 3) == 0 && nxt < kNWin) {
            asm volatile("bar.sync %0, 128;" ::"r"((tid_now() >> 7) + 1) : "memory");
            if (elect_one()) {
                const uint32_t wgl = tid_now() >> 7;
                const uint32_t bar = sbase + kOffBar + 8 * wgl;
                mbar_expect_tx(bar, kXBytes);
                tma_load_x(sbase + kOffX + wgl * kXBytes, &tmx, bar, nxt);
            }
            __syncwarp();
        } else {
            asm volatile("bar.arrive %0, 128;" ::"r"((tid_now() >> 7) + 1) : "memory");
        }
        if (st & kVeryFirst) v_check(st);
        fence_regs(acc);
#pragma unroll
        for (int i = 0; i < 48; i++) fa[i] = pack_bf16(acc[2 * i], acc[2 * i + 1]);

        asm volatile("st.volatile.shared.v4.b32 [%4], {%0, %1, %2, %3};"
                     :: "r"(fa[44]), "r"(fa[45]), "r"(fa[46]), "r"(fa[47]), "r"(sbase + kOffStash + (tid_now() & 127) * 16) : "memory");
        fence_regs(fa);
        if (((tid_now() >> 5) & 3) == 0 && nxt + kPfMin < kNWin) {
            if (elect_one()) {
                const int base = kNWG * G, t = nxt - base;
                const int hi = min(nxt + pf_lead(t, G), kNWin - 1);
                int lo = max(max(nxt - 1 + pf_lead(t - 1, G), nxt) + 1, base + kPfInit * G);
#pragma unroll 1
                for (; lo <= hi; lo++) prefetch_x(&tmp, lo);
            }
            __syncwarp();
        }
        if (nxt >= kNWin) {
            finish_last(fa, dWv, tmo.m, st);
            return;
        }
        lnk = baton_wait(st, fa[43]);
        wg_fence();
        Gemm4<0, 1>::run(acc, fa, dWv);
        wg_commit();
        Gemm4<2, 10>::run(acc, fa, dWv);
        wg_commit();
        wg_wait1();
        uint32_t fl[4];
        asm volatile("ld.volatile.shared.v4.b32 {%0, %1, %2, %3}, [%4];"
                     : "=r"(fl[0]), "=r"(fl[1]), "=r"(fl[2]), "=r"(fl[3]) : "r"(sbase + kOffStash + (tid_now() & 127) * 16) : "memory");
        wg_fence();
        wg192_rs<false, 0, koff(11, 24576)>(acc, fl, dWv);
        wg_commit();
        baton_pass(lnk, st);
        st = ((st ^ kPhase) & (kPhase | kSolo)) | st_win(st) << 4 | nxt << 17;
        uint32_t landed;
        asm volatile("{\n.reg .pred p;\nmbarrier.test_wait.parity.shared::cta.b64 p, [%1], %2;\nselp.b32 %0, 1, 0, p;\n}\n"
                     : "=r"(landed) : "r"(sbase + kOffBar + 8 * (tid_now() >> 7)), "r"(st & kPhase) : "memory");
        wg_wait0();
        fence_regs(acc);
        fence_regs(fa);
        fence_regs(fl);

#pragma unroll
        for (int a = 0; a < 6; a++)
#pragma unroll
            for (int r = 0; r < 2; r++)
                hv[2 * a + r] = make_uint4(pack_bf16(acc[16 * a + 2 * r], acc[16 * a + 2 * r + 1]), pack_bf16(acc[16 * a + 2 * r + 4], acc[16 * a + 2 * r + 5]),
                                           pack_bf16(acc[16 * a + 2 * r + 8], acc[16 * a + 2 * r + 9]), pack_bf16(acc[16 * a + 2 * r + 12], acc[16 * a + 2 * r + 13]));
        if (!landed) mbar_wait(sbase + kOffBar + 8 * (tid_now() >> 7), st & kPhase);
    }
}

typedef CUresult (*EncodeTiledFn)(CUtensorMap*, CUtensorMapDataType, cuuint32_t, void*, const cuuint64_t*,
                                  const cuuint64_t*, const cuuint32_t*, const cuuint32_t*, CUtensorMapInterleave,
                                  CUtensorMapSwizzle, CUtensorMapL2promotion, CUtensorMapFloatOOBfill);

}

extern "C" void kernel_launch(void* const* d_in, const int* in_sizes, int n_in, void* d_out, int out_size) {
    (void)in_sizes; (void)n_in; (void)out_size;
    const __nv_bfloat16* x    = (const __nv_bfloat16*)d_in[0];
    const __nv_bfloat16* wqkv = (const __nv_bfloat16*)d_in[1];
    const __nv_bfloat16* wo   = (const __nv_bfloat16*)d_in[2];

    static EncodeTiledFn encode = nullptr;
    static int num_sms = 0;
    static Scratch* scratch = nullptr;
    if (!encode) {
        void* fn = nullptr;
        cudaDriverEntryPointQueryResult qr;
        cudaGetDriverEntryPoint("cuTensorMapEncodeTiled", &fn, cudaEnableDefault, &qr);
        encode = (EncodeTiledFn)fn;
        cudaGetSymbolAddress((void**)&scratch, g_scratch);
        int dev = 0;
        cudaGetDevice(&dev);
        cudaDeviceGetAttribute(&num_sms, cudaDevAttrMultiProcessorCount, dev);
        cudaFuncSetAttribute(swin_attn_kernel, cudaFuncAttributeMaxDynamicSharedMemorySize, kSmemBytes);
    }
    CUtensorMap tmx;
    const cuuint64_t gdim[4] = {64, (cuuint64_t)kHW, (cuuint64_t)kHW, 3};
    const cuuint64_t gstr[3] = {(cuuint64_t)kC * 2, (cuuint64_t)kHW * kC * 2, 128};
    const cuuint32_t box[4] = {64, 8, 8, 3};
    const cuuint32_t estr[4] = {1, 1, 1, 1};
    encode(&tmx, CU_TENSOR_MAP_DATA_TYPE_BFLOAT16, 4, (void*)x, gdim, gstr, box, estr, CU_TENSOR_MAP_INTERLEAVE_NONE,
           CU_TENSOR_MAP_SWIZZLE_128B, CU_TENSOR_MAP_L2_PROMOTION_NONE, CU_TENSOR_MAP_FLOAT_OOB_FILL_NONE);

    CUtensorMap tmp;
    const cuuint64_t pdim[3] = {(cuuint64_t)kC, (cuuint64_t)kHW, (cuuint64_t)kHW};
    const cuuint64_t pstr[2] = {(cuuint64_t)kC * 2, (cuuint64_t)kHW * kC * 2};
    const cuuint32_t pbox[3] = {(cuuint32_t)kC, 8, 8};
    encode(&tmp, CU_TENSOR_MAP_DATA_TYPE_BFLOAT16, 3, (void*)x, pdim, pstr, pbox, estr, CU_TENSOR_MAP_INTERLEAVE_NONE,
           CU_TENSOR_MAP_SWIZZLE_NONE, CU_TENSOR_MAP_L2_PROMOTION_NONE, CU_TENSOR_MAP_FLOAT_OOB_FILL_NONE);
    CUtensorMap tmc;
    const cuuint32_t boxc[4] = {64, 8, 8, 1};
    encode(&tmc, CU_TENSOR_MAP_DATA_TYPE_BFLOAT16, 4, (void*)x, gdim, gstr, boxc, estr, CU_TENSOR_MAP_INTERLEAVE_NONE,
           CU_TENSOR_MAP_SWIZZLE_128B, CU_TENSOR_MAP_L2_PROMOTION_NONE, CU_TENSOR_MAP_FLOAT_OOB_FILL_NONE);
    OutMaps tmo;
    const cuuint32_t boxo[4] = {64, 8, 1, 2};
    encode(&tmo.m[0], CU_TENSOR_MAP_DATA_TYPE_BFLOAT16, 4, d_out, gdim, gstr, boxo, estr, CU_TENSOR_MAP_INTERLEAVE_NONE,
           CU_TENSOR_MAP_SWIZZLE_128B, CU_TENSOR_MAP_L2_PROMOTION_NONE, CU_TENSOR_MAP_FLOAT_OOB_FILL_NONE);
    const cuuint64_t odim[4] = {64, (cuuint64_t)kHW, (cuuint64_t)kHW, 2};
    const cuuint64_t ostr[3] = {(cuuint64_t)kC * 2, (cuuint64_t)kHW * kC * 2, (cuuint64_t)kHW * kC * 2 - 256};
    encode(&tmo.m[1], CU_TENSOR_MAP_DATA_TYPE_BFLOAT16, 4, (char*)d_out + 256, odim, ostr, boxo, estr, CU_TENSOR_MAP_INTERLEAVE_NONE,
           CU_TENSOR_MAP_SWIZZLE_128B, CU_TENSOR_MAP_L2_PROMOTION_NONE, CU_TENSOR_MAP_FLOAT_OOB_FILL_NONE);
    const cuuint32_t boxs[4] = {64, 8, 2, 1};
    encode(&tmo.m[2], CU_TENSOR_MAP_DATA_TYPE_BFLOAT16, 4, d_out, gdim, gstr, boxs, estr, CU_TENSOR_MAP_INTERLEAVE_NONE,
           CU_TENSOR_MAP_SWIZZLE_128B, CU_TENSOR_MAP_L2_PROMOTION_NONE, CU_TENSOR_MAP_FLOAT_OOB_FILL_NONE);
    swin_attn_kernel<<<num_sms, kThreads, kSmemBytes, cudaStreamPerThread>>>(wqkv, wo, scratch, d_out, num_sms, tmo, tmx, tmp, tmc);
}
```

```cpp
#include <cuda_runtime.h>
#include <cuda_bf16.h>
#include <cuda.h>
#include <stdint.h>

namespace {

constexpr int kC      = 192;
constexpr int kHW     = 512;
constexpr int kNWin   = 4096;
constexpr int kXBytes = 64 * kC * 2;
constexpr int kWBytes = kC * kC * 2;
constexpr int kNWG    = 3;
constexpr int kThreads = kNWG * 128;
constexpr int kTiles  = 144;
constexpr int kPfInit = 2, kPfUp = 160, kPfPeak = 400, kPfHold = 800, kPfDown1 = 40, kPfBase2 = 300, kPfDown2 = 12, kPfMin = 140;
__device__ __forceinline__ int pf_lead(int t, int G) {
    return min(min(kPfInit * G + ((t * kPfUp) >> 8), kPfPeak),
               max(max(kPfPeak - (((t - kPfHold) * kPfDown1) >> 8), kPfBase2 - ((t * kPfDown2) >> 8)), kPfMin));
}
constexpr int kEvictFrom = 3100;
constexpr int kPaceStart = 100, kPaceSpread = 500, kPaceStep0 = 750, kPaceMid = 2100, kPaceStep = 550, kPacePf = 5400, kPaceStepPf = 1000;
constexpr uint32_t kMqkHint = 72;
constexpr uint32_t kPollDelay = 200;
constexpr uint32_t kWvoDelay = 1000;

constexpr int kOffWm  = 0;
constexpr int kOffWv  = kWBytes;
constexpr int kOffX   = 2 * kWBytes;
constexpr int kOffStage = kOffX + kNWG * kXBytes;
constexpr int kOffStash = kOffStage + 8192;
constexpr int kOffBar = kOffStash + 2048;
constexpr int kSmemBytes = kOffBar + 256;
constexpr uint32_t kSmemBase = 1024;

struct Scratch {
    uint32_t ticket[32];
    uint32_t epoch[32];
    uint32_t cnt_v[32];
    uint32_t cnt_m[32];
    uint4 img[2][2][kWBytes / 16];
};
__device__ __align__(128) Scratch g_scratch;

__device__ __forceinline__ uint32_t smem_u32(const void* p) { return (uint32_t)__cvta_generic_to_shared(p); }

__device__ __forceinline__ void mbar_init(uint32_t bar, uint32_t count) {
    asm volatile("mbarrier.init.shared::cta.b64 [%0], %1;" ::"r"(bar), "r"(count) : "memory");
}
__device__ __forceinline__ void mbar_expect_tx(uint32_t bar, uint32_t bytes) {
    asm volatile("mbarrier.arrive.expect_tx.shared::cta.b64 _, [%0], %1;" ::"r"(bar), "r"(bytes) : "memory");
}
__device__ __forceinline__ void mbar_wait(uint32_t bar, uint32_t parity) {
    uint32_t ok;
    uint32_t spins = 0;
    do {
        asm volatile("{\n.reg .pred p;\n"
                     "mbarrier.try_wait.parity.shared::cta.b64 p, [%1], %2;\n"
                     "selp.b32 %0, 1, 0, p;\n}\n"
                     : "=r"(ok) : "r"(bar), "r"(parity) : "memory");
        if (++spins > (1u << 26)) __trap();
    } while (!ok);
}
__device__ __forceinline__ uint32_t tid_now() {
    uint32_t t;
    asm volatile("mov.u32 %0, %%tid.x;" : "=r"(t));
    return t;
}
__device__ __forceinline__ bool elect_one() {
    uint32_t pred;
    asm volatile("{\n.reg .pred p;\nelect.sync _|p, 0xffffffff;\nselp.b32 %0, 1, 0, p;\n}\n" : "=r"(pred));
    return pred != 0;
}
__device__ __forceinline__ uint32_t wg_uniform() { return __reduce_or_sync(0xffffffffu, tid_now() >> 7); }
constexpr uint32_t kLink = kSmemBase + kOffBar + 64;
constexpr uint32_t kMarks = kLink + 24;
constexpr uint32_t kPhase = 1;
constexpr uint32_t kSolo = 2;
constexpr uint32_t kFirst = 4;
constexpr uint32_t kRound = 8;
constexpr uint32_t kVeryFirst = 1u << 16;
__device__ __forceinline__ int st_out(uint32_t st) { return (st >> 4) & 0xfff; }
__device__ __forceinline__ int st_win(uint32_t st) { return st >> 17; }
__device__ __forceinline__ uint32_t baton_wait(uint32_t st, uint32_t packed) {
    if (packed == 0xffffffffu) __trap();
    if (!(st & kSolo)) asm volatile("bar.sync %0, 256;" ::"r"((tid_now() >> 7) + 8) : "memory");
    uint32_t lnk;
    asm volatile("ld.volatile.shared.u32 %0, [%1];" : "=r"(lnk) : "r"(kLink + 8 * (tid_now() >> 7)) : "memory");
    return lnk;
}
__device__ __forceinline__ uint32_t baton_wait_pub(uint32_t st, uint32_t packed, uint32_t& pub) {
    if (packed == 0xffffffffu) __trap();
    asm volatile("bar.sync %0, %1;" ::"r"((tid_now() >> 7) + 8), "r"(st & kSolo ? 128 : 256) : "memory");
    uint32_t lnk;
    asm volatile("ld.volatile.shared.v2.u32 {%0, %1}, [%2];" : "=r"(lnk), "=r"(pub) : "r"(kLink + 8 * (tid_now() >> 7)) : "memory");
    return lnk;
}
__device__ __forceinline__ void baton_pass(uint32_t lnk, uint32_t& st) {
    const bool other = lnk != (tid_now() >> 7) + 8;
    if (other) asm volatile("bar.arrive %0, 256;" ::"r"(lnk) : "memory");
    st = other ? st & ~kSolo : st | kSolo;
}
__device__ __forceinline__ void set_link(int w, uint32_t v) { asm volatile("st.volatile.shared.u32 [%0], %1;" ::"r"(kLink + 8 * w), "r"(v) : "memory"); }
constexpr uint64_t kPolNormal = 0x1000000000000000ull, kPolFirst = 0x12F0000000000000ull;
__device__ __forceinline__ void tma_load_x(uint32_t dst, const CUtensorMap* tm, uint32_t bar, int win) {
    const int wh = win >> 6, ww = win & 63;
    asm volatile("cp.async.bulk.tensor.4d.shared::cluster.global.mbarrier::complete_tx::bytes.L2::cache_hint"
                 " [%0], [%1, {%3, %4, %5, %6}], [%2], %7;"
                 ::"r"(dst), "l"(tm), "r"(bar), "r"(0), "r"(ww * 8), "r"(wh * 8), "r"(0), "l"(win >= kEvictFrom ? kPolFirst : kPolNormal) : "memory");
}
__device__ __forceinline__ void tma_load_x_chunk(uint32_t dst, const CUtensorMap* tm, uint32_t bar, int win, int chunk) {
    const int wh = win >> 6, ww = win & 63;
    asm volatile("cp.async.bulk.tensor.4d.shared::cluster.global.mbarrier::complete_tx::bytes"
                 " [%0], [%1, {%3, %4, %5, %6}], [%2];"
                 ::"r"(dst), "l"(tm), "r"(bar), "r"(0), "r"(ww * 8), "r"(wh * 8), "r"(chunk) : "memory");
}
__device__ __forceinline__ void bulk_load(uint32_t dst, const void* src, uint32_t bytes, uint32_t bar) {
    asm volatile("cp.async.bulk.shared::cluster.global.mbarrier::complete_tx::bytes [%0], [%1], %2, [%3];"
                 ::"r"(dst), "l"(src), "r"(bytes), "r"(bar) : "memory");
}

__device__ __forceinline__ void wg_fence()  { asm volatile("wgmma.fence.sync.aligned;" ::: "memory"); }
__device__ __forceinline__ void wg_commit() { asm volatile("wgmma.commit_group.sync.aligned;" ::: "memory"); }
__device__ __forceinline__ void wg_wait0()  { asm volatile("wgmma.wait_group.sync.aligned 0;" ::: "memory"); }
__device__ __forceinline__ void wg_wait1()  { asm volatile("wgmma.wait_group.sync.aligned 1;" ::: "memory"); }
__device__ __forceinline__ void wg_wait2()  { asm volatile("wgmma.wait_group.sync.aligned 2;" ::: "memory"); }

template <int N> __device__ __forceinline__ void fence_regs(float (&d)[N]) {
#pragma unroll
    for (int i = 0; i < N; i++) asm volatile("" : "+f"(d[i])::"memory");
}
template <int N> __device__ __forceinline__ void fence_regs(uint32_t (&d)[N]) {
#pragma unroll
    for (int i = 0; i < N; i++) asm volatile("" : "+r"(d[i])::"memory");
}

#define ACC8(c, d, i) c(d[i]), c(d[i + 1]), c(d[i + 2]), c(d[i + 3]), c(d[i + 4]), c(d[i + 5]), c(d[i + 6]), c(d[i + 7])
#define ACC32(c, d) ACC8(c, d, 0), ACC8(c, d, 8), ACC8(c, d, 16), ACC8(c, d, 24)
#define ACC96(c, d) ACC32(c, d), ACC8(c, d, 32), ACC8(c, d, 40), ACC8(c, d, 48), ACC8(c, d, 56), \
                    ACC8(c, d, 64), ACC8(c, d, 72), ACC8(c, d, 80), ACC8(c, d, 88)
#define C_IO(x) "+f"(x)
#define C_O(x) "=f"(x)
#define REGS32 "{%0, %1, %2, %3, %4, %5, %6, %7, %8, %9, %10, %11, %12, %13, %14, %15, " \
               "%16, %17, %18, %19, %20, %21, %22, %23, %24, %25, %26, %27, %28, %29, %30, %31}"
#define REGS96 "{%0, %1, %2, %3, %4, %5, %6, %7, %8, %9, %10, %11, %12, %13, %14, %15, " \
               "%16, %17, %18, %19, %20, %21, %22, %23, %24, %25, %26, %27, %28, %29, %30, %31, " \
               "%32, %33, %34, %35, %36, %37, %38, %39, %40, %41, %42, %43, %44, %45, %46, %47, " \
               "%48, %49, %50, %51, %52, %53, %54, %55, %56, %57, %58, %59, %60, %61, %62, %63, " \
               "%64, %65, %66, %67, %68, %69, %70, %71, %72, %73, %74, %75, %76, %77, %78, %79, " \
               "%80, %81, %82, %83, %84, %85, %86, %87, %88, %89, %90, %91, %92, %93, %94, %95}"

#define DESC_HI "0x40000040"
#define MK_DESC(name, lo, off) "add.u32 t, " lo ", " off ";\nmov.b64 " name ", {t, " DESC_HI "};\n"

template <bool First, int OA, int OB> __device__ __forceinline__ void wg192_ss(float (&d)[96], uint32_t la, uint32_t lb) {
    if constexpr (First)
        asm volatile("{\n.reg .pred p;\n.reg .b32 t;\n.reg .b64 da, db;\nsetp.ne.b32 p, 0, 0;\n"
                     MK_DESC("da", "%96", "%98") MK_DESC("db", "%97", "%99")
                     "wgmma.mma_async.sync.aligned.m64n192k16.f32.bf16.bf16 " REGS96 ", da, db, p, 1, 1, 0, 0;\n}\n"
                     : ACC96(C_O, d) : "r"(la), "r"(lb), "n"(OA), "n"(OB));
    else
        asm volatile("{\n.reg .pred p;\n.reg .b32 t;\n.reg .b64 da, db;\nsetp.ne.b32 p, 1, 0;\n"
                     MK_DESC("da", "%96", "%98") MK_DESC("db", "%97", "%99")
                     "wgmma.mma_async.sync.aligned.m64n192k16.f32.bf16.bf16 " REGS96 ", da, db, p, 1, 1, 0, 0;\n}\n"
                     : ACC96(C_IO, d) : "r"(la), "r"(lb), "n"(OA), "n"(OB));
}
template <bool First, int TB, int OB> __device__ __forceinline__ void wg192_rs(float (&d)[96], const uint32_t* a, uint32_t lb) {
    if constexpr (First)
        asm volatile("{\n.reg .pred p;\n.reg .b32 t;\n.reg .b64 db;\nsetp.ne.b32 p, 0, 0;\n"
                     MK_DESC("db", "%100", "%102")
                     "wgmma.mma_async.sync.aligned.m64n192k16.f32.bf16.bf16 " REGS96 ", {%96, %97, %98, %99}, db, p, 1, 1, %101;\n}\n"
                     : ACC96(C_O, d) : "r"(a[0]), "r"(a[1]), "r"(a[2]), "r"(a[3]), "r"(lb), "n"(TB), "n"(OB));
    else
        asm volatile("{\n.reg .pred p;\n.reg .b32 t;\n.reg .b64 db;\nsetp.ne.b32 p, 1, 0;\n"
                     MK_DESC("db", "%100", "%102")
                     "wgmma.mma_async.sync.aligned.m64n192k16.f32.bf16.bf16 " REGS96 ", {%96, %97, %98, %99}, db, p, 1, 1, %101;\n}\n"
                     : ACC96(C_IO, d) : "r"(a[0]), "r"(a[1]), "r"(a[2]), "r"(a[3]), "r"(lb), "n"(TB), "n"(OB));
}
template <bool First, int TB, int OB> __device__ __forceinline__ void wg64_rs(float (&d)[32], const uint32_t* a, uint32_t lb) {
    if constexpr (First)
        asm volatile("{\n.reg .pred p;\n.reg .b32 t;\n.reg .b64 db;\nsetp.ne.b32 p, 0, 0;\n"
                     MK_DESC("db", "%36", "%38")
                     "wgmma.mma_async.sync.aligned.m64n64k16.f32.bf16.bf16 " REGS32 ", {%32, %33, %34, %35}, db, p, 1, 1, %37;\n}\n"
                     : ACC32(C_O, d) : "r"(a[0]), "r"(a[1]), "r"(a[2]), "r"(a[3]), "r"(lb), "n"(TB), "n"(OB));
    else
        asm volatile("{\n.reg .pred p;\n.reg .b32 t;\n.reg .b64 db;\nsetp.ne.b32 p, 1, 0;\n"
                     MK_DESC("db", "%36", "%38")
                     "wgmma.mma_async.sync.aligned.m64n64k16.f32.bf16.bf16 " REGS32 ", {%32, %33, %34, %35}, db, p, 1, 1, %37;\n}\n"
                     : ACC32(C_IO, d) : "r"(a[0]), "r"(a[1]), "r"(a[2]), "r"(a[3]), "r"(lb), "n"(TB), "n"(OB));
}
template <int OB> __device__ __forceinline__ void wg64_rs_reuse(float (&d)[32], const uint32_t* a, uint32_t lb, uint32_t one) {
    asm volatile("{\n.reg .pred p;\n.reg .b32 t;\n.reg .b64 db;\nsetp.ne.b32 p, %38, 1;\n"
                 MK_DESC("db", "%36", "%37")
                 "wgmma.mma_async.sync.aligned.m64n64k16.f32.bf16.bf16 " REGS32 ", {%32, %33, %34, %35}, db, p, 1, 1, 0;\n}\n"
                 : ACC32(C_IO, d) : "r"(a[0]), "r"(a[1]), "r"(a[2]), "r"(a[3]), "r"(lb), "n"(OB), "r"(one));
}
__host__ __device__ constexpr int koff(int kk, int chunk) { return ((kk >> 2) * chunk + (kk & 3) * 32) >> 4; }

__device__ __forceinline__ void stsm4(uint32_t addr, const uint4& v) {
    asm volatile("stmatrix.sync.aligned.m8n8.x4.shared.b16 [%0], {%1, %2, %3, %4};" ::"r"(addr), "r"(v.x), "r"(v.y), "r"(v.z), "r"(v.w) : "memory");
}
__device__ __forceinline__ void bulk_wait_read() {
    asm volatile("cp.async.bulk.wait_group.read 0;" ::: "memory");
}
__device__ __forceinline__ uint32_t stage_addr(uint32_t slot, uint32_t l) { return slot + (l & 7) * 128 + ((((l >> 3) & 3) ^ (l & 7)) << 4); }
__device__ __forceinline__ void stage_fence() {
    asm volatile("fence.proxy.async.shared::cta;" ::: "memory");
    __syncwarp();
}
template <int R> __device__ __forceinline__ void store_round(const uint4 (&h)[12], uint32_t slot, const CUtensorMap* tm, int col, int row) {
    const uint32_t sa = stage_addr(slot, tid_now());
#pragma unroll
    for (int i = 0; i < 2; i++) {
        const int r = (2 * R + i) / 3, c = (2 * R + i) % 3;
        stsm4(sa + i * 1024, h[4 * c + r]);
        stsm4((sa ^ 64) + i * 1024, h[4 * c + 2 + r]);
    }
    stage_fence();
    asm volatile("{\n.reg .pred p;\nelect.sync _|p, 0xffffffff;\n"
                 "@p cp.async.bulk.tensor.4d.global.shared::cta.bulk_group [%0, {%2, %3, %4, %5}], [%1];\n"
                 "@p cp.async.bulk.commit_group;\n}\n"
                 ::"l"(tm + (R == 1)), "r"(slot), "r"(0), "r"(col), "r"(row + (R == 2)), "r"((int)(R == 2)) : "memory");
}
__device__ __forceinline__ uint32_t warp4_uniform() { return __reduce_or_sync(0xffffffffu, (tid_now() >> 5) & 3); }
struct OutMaps { CUtensorMap m[3]; };
__host__ __device__ constexpr uint32_t bar_m(int c) { return kSmemBase + kOffBar + 32 + 8 * c; }
__device__ __forceinline__ void m_load(const Scratch* sc, int c, uint32_t par) {
    mbar_expect_tx(bar_m(c), 24576);
    bulk_load(kSmemBase + kOffWm + c * 24576, sc->img[par][0] + c * 1536, 24576, bar_m(c));
}
__device__ __forceinline__ bool m_agree(uint32_t ok) {
    uint32_t all;
    asm volatile("{\n.reg .pred p, q;\nsetp.ne.u32 p, %1, 0;\nbar.red.and.pred q, 7, 256, p;\nselp.b32 %0, 1, 0, q;\n}\n" : "=r"(all) : "r"(ok) : "memory");
    return all != 0;
}
__device__ __forceinline__ void m_check(const Scratch* sc, uint32_t par) {
    for (uint32_t round = 0;; round++) {
        uint32_t m = ~0u;
#pragma unroll 1
        for (int c = 0; c < 3; c++) {
            mbar_wait(bar_m(c), round & 1);
#pragma unroll
            for (int j = 0; j < 6; j++) {
                uint32_t v;
                asm volatile("ld.volatile.shared.b32 %0, [%1];" : "=r"(v)
                             : "r"(kSmemBase + kOffWm + c * 24576 + 4096 * j + (tid_now() & 127) * 32 + (tid_now() & 28)) : "memory");
                m = min(m, v);
            }
        }
        if (m_agree(m)) break;
        asm volatile("bar.sync 7, 256;" ::: "memory");
        if (round > (1u << 20)) __trap();
        if (tid_now() == 128) {
            m_load(sc, 0, par); m_load(sc, 1, par); m_load(sc, 2, par);
        }
    }
}
constexpr uint32_t kBarV = kSmemBase + kOffBar + 56;
__device__ __forceinline__ void v_load(const Scratch* sc, uint32_t par) {
    mbar_expect_tx(kBarV, kWBytes);
#pragma unroll 1
    for (int c = 0; c < 3; c++) bulk_load(kSmemBase + kOffWv + c * 24576, sc->img[par][1] + c * 1536, 24576, kBarV);
}
constexpr uint32_t kScAddr = kSmemBase + kOffBar + 96;
__device__ __forceinline__ void v_check(uint32_t st) {
    for (uint32_t round = 0;; round++) {
        mbar_wait(kBarV, round & 1);
        uint32_t m = ~0u;
#pragma unroll
        for (int j = 0; j < 18; j++) {
            uint32_t v;
            asm volatile("ld.volatile.shared.b32 %0, [%1];" : "=r"(v)
                         : "r"(kSmemBase + kOffWv + 4096 * j + (tid_now() & 127) * 32 + (tid_now() & 28)) : "memory");
            m = min(m, v);
        }
        uint32_t all;
        asm volatile("{\n.reg .pred p, q;\nsetp.ne.u32 p, %1, 0;\nbar.red.and.pred q, 14, 128, p;\nselp.b32 %0, 1, 0, q;\n}\n" : "=r"(all) : "r"(m) : "memory");
        if (all) break;
        if (round > (1u << 20)) __trap();
        if (tid_now() == 0) {
            const Scratch* q;
            asm volatile("ld.volatile.shared.u64 %0, [%1];" : "=l"(q) : "r"(kScAddr) : "memory");
            v_load(q, st_out(st));
        }
    }
}
__host__ __device__ constexpr uint32_t bar_x(int w, int c) { return kSmemBase + kOffBar + 128 + 32 * w + 8 * c; }
template <int K> struct Gemm1 {
    static __device__ __forceinline__ void run(float (&d)[96], uint32_t lx, uint32_t lw, bool very_first, uint32_t st) {
        if constexpr (K > 0) Gemm1<K - 1>::run(d, lx, lw, very_first, st);
        if constexpr (K == 0 || K == 4 || K == 8) {
            if constexpr (K == 0) {
                if (very_first) mbar_wait(bar_m(0), (st & kRound) != 0);
            } else if (st & kFirst) {
                mbar_wait(bar_x(0, K / 4) + 32 * (tid_now() >> 7), 0);
                if (very_first) mbar_wait(bar_m(K / 4), (st & kRound) != 0);
            }
            wg_fence();
        }
        wg192_ss<K == 0, koff(K, 8192), koff(K, 24576)>(d, lx, lw);
    }
};
__device__ __forceinline__ void draw_ticket(uint32_t& ticket) {
    asm volatile("{\n.reg .pred p;\n.reg .b64 a;\nsetp.eq.u32 p, %1, 0;\nld.volatile.shared.u64 a, [%3];\n"
                 "@p atom.relaxed.gpu.global.inc.u32 %0, [a], %2;\n}\n"
                 : "+r"(ticket) : "r"(tid_now() & 127), "n"(kNWin - 1), "r"(kScAddr) : "memory");
}
template <int KK> struct Gemm2 { static __device__ __forceinline__ void run(float (&d)[32], const uint32_t* a, uint32_t lx, uint32_t lnk, uint32_t& st) {
    Gemm2<KK - 1>::run(d, a, lx, lnk, st); wg64_rs<KK == 0, 0, koff(KK, 8192)>(d, a + 4 * KK, lx);
    if constexpr (KK == 9) {
        __syncwarp();
        bulk_wait_read();
        baton_pass(lnk, st);
    } } };
template <> struct Gemm2<-1> { static __device__ __forceinline__ void run(float (&)[32], const uint32_t*, uint32_t, uint32_t, uint32_t&) {} };
template <int KK> struct Gemm3 { static __device__ __forceinline__ void run(float (&d)[96], const uint32_t* a, uint32_t lxt) {
    Gemm3<KK - 1>::run(d, a, lxt); wg192_rs<KK == 0, 1, KK * (2048 >> 4)>(d, a + 4 * KK, lxt); } };
template <> struct Gemm3<-1> { static __device__ __forceinline__ void run(float (&)[96], const uint32_t*, uint32_t) {} };
template <int K0, int KK> struct Gemm4 { static __device__ __forceinline__ void run(float (&d)[96], const uint32_t* a, uint32_t lw) {
    if constexpr (KK > K0) Gemm4<K0, KK - 1>::run(d, a, lw);
    wg192_rs<KK == 0, 0, koff(KK, 24576)>(d, a + 4 * KK, lw); } };

template <int C, int KK> struct Gemm3s { static __device__ __forceinline__ void run(float (&d)[32], const uint32_t* a, uint32_t lxt) {
    if constexpr (KK > 0) Gemm3s<C, KK - 1>::run(d, a, lxt);
    wg64_rs<KK == 0, 1, (C * 8192 + KK * 2048) / 16>(d, a + 4 * KK, lxt); } };
template <int C, int K0, int KK> struct Gemm4s { static __device__ __forceinline__ void run(float (&d)[32], const uint32_t* a, uint32_t lw, uint32_t one) {
    if constexpr (KK > K0) Gemm4s<C, K0, KK - 1>::run(d, a, lw, one);
    if constexpr (KK == 0) wg64_rs_reuse<C * 8192 / 16>(d, a, lw, one);
    else wg64_rs<false, 0, koff(KK, 24576) + C * 8192 / 16>(d, a + 4 * KK, lw); } };

__device__ __forceinline__ uint32_t pack_bf16(float lo, float hi) {
    uint32_t r;
    asm("cvt.rn.bf16x2.f32 %0, %1, %2;" : "=r"(r) : "f"(hi), "f"(lo));
    return r;
}
__device__ __forceinline__ float ex2(float x) {
    float r;
    asm("ex2.approx.ftz.f32 %0, %1;" : "=f"(r) : "f"(x));
    return r;
}
__device__ __forceinline__ float rcp(float x) {
    float r;
    asm("rcp.approx.ftz.f32 %0, %1;" : "=f"(r) : "f"(x));
    return r;
}
__device__ __forceinline__ void mma16816(float (&c)[4], uint32_t a0, uint32_t a1, uint32_t a2, uint32_t a3,
                                         uint32_t b0, uint32_t b1) {
    asm volatile("mma.sync.aligned.m16n8k16.row.col.f32.bf16.bf16.f32 {%0,%1,%2,%3}, {%4,%5,%6,%7}, {%8,%9}, {%0,%1,%2,%3};"
                 : "+f"(c[0]), "+f"(c[1]), "+f"(c[2]), "+f"(c[3])
                 : "r"(a0), "r"(a1), "r"(a2), "r"(a3), "r"(b0), "r"(b1));
}

struct FoldRegs { uint4 B0[6], B1[6]; uint32_t A[48]; };

__device__ __forceinline__ void st_relaxed64(void* p, uint32_t a, uint32_t b, uint32_t on) {
    asm volatile("{\n.reg .pred q;\nsetp.ne.u32 q, %3, 0;\n@q st.relaxed.gpu.global.v2.b32 [%0], {%1, %2};\n}\n" ::"l"(p), "r"(a), "r"(b), "r"(on) : "memory");
}
__device__ __forceinline__ uint32_t pack_nonzero(float lo, float hi) { const uint32_t v = pack_bf16(lo, hi); return v != 0 ? v : 0x80000000u; }
__device__ __forceinline__ void fold_store(char* img, uint32_t* cnt, uint32_t epoch, uint32_t on, uint32_t zero, int n_lo, int n_hi, int k0, int lane, const float (&c0)[4], const float (&c1)[4]) {
    const int q = lane & 3;
    const int u = ((k0 & 63) >> 3) + (q >> 1);
    const int base = (k0 >> 6) * 24576 + (q & 1) * 8;
    char* p_lo = img + (base + n_lo * 128 + ((u ^ (n_lo & 7)) << 4));
    char* p_hi = img + (base + n_hi * 128 + ((u ^ (n_hi & 7)) << 4));
    const uint32_t v0 = pack_nonzero(c0[0], c0[1]);
    const uint32_t par = (epoch & 1) | (v0 & zero);
    st_relaxed64(p_lo + par * (2 * kWBytes), v0, pack_nonzero(c1[0], c1[1]), on);
    st_relaxed64(p_hi + par * (2 * kWBytes), pack_nonzero(c0[2], c0[3]), pack_nonzero(c1[2], c1[3]), on);
    asm volatile("{\n.reg .pred q;\nsetp.ne.u32 q, %1, 0;\n@q red.relaxed.gpu.global.inc.u32 [%0], 0xffff;\n}\n" ::"l"(cnt), "r"(lane == 0 ? on : 0u) : "memory");
    st_relaxed64(p_lo + (par ^ 1) * (2 * kWBytes), 0, 0, on);
    st_relaxed64(p_hi + (par ^ 1) * (2 * kWBytes), 0, 0, on);
}
__device__ __forceinline__ void fold_load_qk(FoldRegs& r, const __nv_bfloat16* __restrict__ wqkv, int tile, int lane) {
    const int g = lane >> 2, q = lane & 3;
    const uint32_t tn = (uint32_t)tile * 171 >> 11, tk = tile - 12 * tn;
    uint32_t oa = tn * (16 * 1152) + (g * 1152 + 16 * q), ob = tk * (16 * 1152) + ((4 * (g >> 1) + (g & 1)) * 1152 + 16 * q);
    asm("" : "+r"(oa), "+r"(ob));
    const uint4* pa0 = reinterpret_cast<const uint4*>(reinterpret_cast<const char*>(wqkv) + oa) + 24;
    const uint4* pa1 = pa0 + 8 * 72;
    const uint4* pb0 = reinterpret_cast<const uint4*>(reinterpret_cast<const char*>(wqkv) + ob);
    const uint4* pb1 = pb0 + 2 * 72;
#pragma unroll
    for (int j = 0; j < 6; j++) {
        const uint4 lo = __ldg(pa0 + 4 * j), hi = __ldg(pa1 + 4 * j);
        r.A[8 * j + 0] = lo.x; r.A[8 * j + 1] = hi.x; r.A[8 * j + 2] = lo.y; r.A[8 * j + 3] = hi.y;
        r.A[8 * j + 4] = lo.z; r.A[8 * j + 5] = hi.z; r.A[8 * j + 6] = lo.w; r.A[8 * j + 7] = hi.w;
        r.B0[j] = __ldg(pb0 + 4 * j);
        r.B1[j] = __ldg(pb1 + 4 * j);
    }
}
__device__ __forceinline__ void fold_load_vo(FoldRegs& r, const __nv_bfloat16* __restrict__ wqkv, const __nv_bfloat16* __restrict__ wo,
                                             int tile, int lane) {
    const int g = lane >> 2, q = lane & 3;
    const int ch0 = (tile / 12) * 16 + 2 * g;
    const int k0 = (tile % 12) * 16;
    const int kb = k0 + 4 * (g >> 1) + (g & 1);
    const uint4* pb0 = reinterpret_cast<const uint4*>(wqkv + (size_t)kb * 576 + 384 + 8 * q);
    const uint4* pb1 = reinterpret_cast<const uint4*>(wqkv + (size_t)(kb + 2) * 576 + 384 + 8 * q);
    const uint32_t* pw = reinterpret_cast<const uint32_t*>(wo + (size_t)(8 * q) * kC + ch0);
#pragma unroll
    for (int j = 0; j < 6; j++) {
        r.B0[j] = __ldg(pb0 + 4 * j);
        r.B1[j] = __ldg(pb1 + 4 * j);
#pragma unroll
        for (int i = 0; i < 8; i++) r.A[8 * j + i] = __ldg(pw + (32 * j + i) * (kC / 2));
    }
}
template <bool kVO>
__device__ __forceinline__ void fold_compute_store(FoldRegs& r, Scratch* sc, int tile, int lane, uint32_t epoch, uint32_t on, uint32_t zero) {
    const int g = lane >> 2;
    float c0[4] = {0.f, 0.f, 0.f, 0.f}, c1[4] = {0.f, 0.f, 0.f, 0.f}, c2[4] = {0.f, 0.f, 0.f, 0.f}, c3[4] = {0.f, 0.f, 0.f, 0.f};
#pragma unroll
    for (int j = 0; j < 6; j++) {
        uint32_t a[8];
        if constexpr (kVO) {
#pragma unroll
            for (int i = 0; i < 4; i++) {
                a[2 * i]     = __byte_perm(r.A[8 * j + 2 * i], r.A[8 * j + 2 * i + 1], 0x5410);
                a[2 * i + 1] = __byte_perm(r.A[8 * j + 2 * i], r.A[8 * j + 2 * i + 1], 0x7632);
            }
        } else {
#pragma unroll
            for (int i = 0; i < 8; i++) asm volatile("prmt.b32 %0, %1, 0, 0x3210;" : "=r"(a[i]) : "r"(r.A[8 * j + i]));
        }
        mma16816(c0, a[0], a[1], a[2], a[3], r.B0[j].x, r.B0[j].y);
        mma16816(c1, a[0], a[1], a[2], a[3], r.B1[j].x, r.B1[j].y);
        mma16816(c2, a[4], a[5], a[6], a[7], r.B0[j].z, r.B0[j].w);
        mma16816(c3, a[4], a[5], a[6], a[7], r.B1[j].z, r.B1[j].w);
    }
#pragma unroll
    for (int i = 0; i < 4; i++) { c0[i] += c2[i]; c1[i] += c3[i]; }
    const int k0 = (tile % 12) * 16;
    if constexpr (kVO) {
        const int n = (tile / 12) * 16 + 2 * g;
        fold_store(reinterpret_cast<char*>(sc->img[0][1]), sc->cnt_v, epoch, on, zero, n, n + 1, k0, lane, c0, c1);
    } else {
        const int n0 = (tile / 12) * 16;
        fold_store(reinterpret_cast<char*>(sc->img[0][0]), sc->cnt_m, epoch, on, zero, n0 + g, n0 + g + 8, k0, lane, c0, c1);
    }
}

__device__ __forceinline__ void prefetch_x(const CUtensorMap* tm, int win) {
    const int wh = win >> 6, ww = win & 63;
    asm volatile("cp.async.bulk.prefetch.tensor.3d.L2.global.tile [%0, {%1, %2, %3}];"
                 ::"l"(tm), "r"(0), "r"(ww * 8), "r"(wh * 8) : "memory");
}

__device__ __forceinline__ void publish(uint32_t ticket) {
    asm volatile("{\n.reg .pred p;\nsetp.eq.u32 p, %2, 0;\n@p st.volatile.shared.u32 [%0], %1;\n}\n"
                 ::"r"(kLink + 4 + 8 * (tid_now() >> 7)), "r"(ticket), "r"(tid_now() & 127) : "memory");
}
__device__ __forceinline__ void reset_for_next_launch() {
    Scratch* q;
    asm volatile("ld.volatile.shared.u64 %0, [%1];" : "=l"(q) : "r"(kScAddr) : "memory");
    q->cnt_v[0] = 0; q->cnt_m[0] = 0; atomicAdd(q->epoch, 1);
}

__device__ __forceinline__ void send_slice(const CUtensorMap* tm, uint32_t slot, uint32_t col, uint32_t row, uint32_t c) {
    stage_fence();
    asm volatile("{\n.reg .pred p;\nelect.sync _|p, 0xffffffff;\n"
                 "@p cp.async.bulk.tensor.4d.global.shared::cta.bulk_group [%0, {%2, %3, %4, %5}], [%1];\n}\n"
                 ::"l"(tm + 2), "r"(slot + c * 2048), "r"(0), "r"(col), "r"(row), "r"(c) : "memory");
}
__device__ __forceinline__ void bulk_commit() { asm volatile("cp.async.bulk.commit_group;" ::: "memory"); }
template <bool AddNz> __device__ __forceinline__ void pack_slice(uint4 (&h)[4], float (&o)[32], float nz) {
    fence_regs(o);
    auto pk = [&](int i) { return pack_bf16(o[i], AddNz ? o[i + 1] + nz : o[i + 1]); };
#pragma unroll
    for (int i = 0; i < 4; i++) {
        const int b = 16 * (i & 1) + 2 * (i >> 1);
        h[i] = make_uint4(pk(b), pk(b + 4), pk(b + 8), pk(b + 12));
    }
#pragma unroll
    for (int i = 0; i < 4; i++) asm volatile("" : "+r"(h[i].x), "+r"(h[i].y), "+r"(h[i].z), "+r"(h[i].w)::"memory");
}
__device__ __forceinline__ void stage_part(uint32_t sa, int c, const uint4 (&h)[4], int i) { stsm4((sa ^ (i & 1) * 64) + (i >> 1) * 1024 + c * 2048, h[i]); }
#define W(C, K0, K1, O) Gemm4s<C, K0, K1>::run(O, fa, dWv, one)
#define W_STAGE(C, O) stage_part(sa, C - 1, h, 0); W(C, 5, 5, O); stage_part(sa, C - 1, h, 1); W(C, 6, 6, O); \
                      stage_part(sa, C - 1, h, 2); W(C, 7, 7, O); stage_part(sa, C - 1, h, 3); W(C, 8, 8, O)

__device__ __forceinline__ void finish_alone(const uint32_t (&pa_in)[16], uint32_t dXt, uint32_t dWv, const CUtensorMap* tm, uint32_t st) {
    uint32_t pa[16];
#pragma unroll
    for (int j = 0; j < 16; j++) pa[j] = pa_in[j];
    char* out;
    asm volatile("ld.volatile.shared.u64 %0, [%1];" : "=l"(out) : "r"(kScAddr + 8) : "memory");
    const uint32_t one = gridDim.y;
    const float nz = __uint_as_float(one << 31);
    float u0[32], u1[32], u2[32];
    float (&o0)[32] = u0, (&o1)[32] = u2, (&o2)[32] = u0;
    uint32_t fa[48];
    uint4 h[4];
    auto pack_a = [&](float (&u)[32], int c) {
        fence_regs(u);
#pragma unroll
        for (int i = 0; i < 16; i++) {
            fa[16 * c + i] = pack_bf16(c != 1 ? u[2 * i] + nz : u[2 * i], u[2 * i + 1]);
            asm volatile("" : "+r"(fa[16 * c + i])::"memory");
        }
        wg_fence();
    };
    const uint32_t t = tid_now(), win = st_win(st);
    const uint32_t slot = kSmemBase + kOffX + (t >> 5) * 6144, sa = stage_addr(slot, t);
    const uint32_t col = (win & 63) * 8, row = (win >> 6) * 8 + ((t >> 4) & 6);
    if (!(st & kSolo)) asm volatile("bar.sync %0, 256;" ::"r"((t >> 7) + 8) : "memory");
    wg_fence();
    Gemm3s<0, 3>::run(u0, pa, dXt); wg_commit();
    Gemm3s<1, 3>::run(u1, pa, dXt); wg_commit();
    Gemm3s<2, 3>::run(u2, pa, dXt); wg_commit();
    wg_wait2(); pack_a(u0, 0);
    W(0, 0, 3, o0); wg_commit();
    wg_wait2(); pack_a(u1, 1);
    W(0, 4, 7, o0); wg_commit();
    wg_wait2(); pack_a(u2, 2);
    W(0, 8, 11, o0); wg_commit();
    W(1, 0, 0, o1);
    asm volatile("bar.sync %0, 128;" ::"r"((t >> 7) + 1) : "memory");
    wg_fence();
    W(1, 1, 4, o1); wg_commit();
    wg_wait1(); pack_slice<true>(h, o0, nz);
    W_STAGE(1, o1);
    W(1, 9, 10, o1);
    send_slice(tm, slot, col, row, 0);
    wg_fence();
    W(1, 11, 11, o1); wg_commit();
    W(2, 0, 4, o2); wg_commit();
    wg_wait1(); pack_slice<false>(h, o1, nz);
    W_STAGE(2, o2);
    W(2, 9, 10, o2);
    send_slice(tm, slot, col, row, 1);
    wg_fence();
    W(2, 11, 11, o2); wg_commit();
    __syncwarp();
    bulk_commit();
    __syncwarp();
    wg_wait0(); pack_slice<false>(h, o2, nz);
    fence_regs(fa);
#pragma unroll
    for (int i = 0; i < 4; i++) stage_part(sa, 2, h, i);
    __syncwarp();
    const uint32_t tok = (t >> 3) & 3, j = t & 7, la = slot + tok * 128 + ((j ^ tok) << 4);
    out += (row * kHW + col + tok) * (kC * 2) + j * 16 + 256;
#pragma unroll
    for (int i = 0; i < 4; i++)
        asm volatile("ld.volatile.shared.v4.b32 {%0, %1, %2, %3}, [%4];" : "=r"(h[i].x), "=r"(h[i].y), "=r"(h[i].z), "=r"(h[i].w)
                     : "r"((la ^ (i & 1) * 64) + i * 512 + 4096) : "memory");
#pragma unroll
    for (int i = 0; i < 4; i++)
        asm volatile("st.global.v4.b32 [%0], {%1, %2, %3, %4};"
                     ::"l"(out + ((i >> 1) * kHW + 4 * (i & 1)) * (kC * 2)), "r"(h[i].x), "r"(h[i].y), "r"(h[i].z), "r"(h[i].w) : "memory");
    __syncwarp();
    bulk_wait_read();
}

__device__ __forceinline__ void finish_last(const uint32_t (&fa_in)[48], uint32_t dWv, const CUtensorMap* tm, uint32_t st) {
    uint32_t fa[48];
#pragma unroll
    for (int j = 0; j < 48; j++) fa[j] = fa_in[j];
    const uint32_t one = gridDim.y;
    const float nz = __uint_as_float(one << 31);
    float o0[32], o1[32];
    float (&o2)[32] = o0;
    uint4 h[4];
    const uint32_t t = tid_now(), win = st_win(st);
    const uint32_t slot = kSmemBase + kOffX + (t >> 5) * 6144, sa = stage_addr(slot, t);
    const uint32_t col = (win & 63) * 8, row = (win >> 6) * 8 + ((t >> 4) & 6);
    const uint32_t la = kLink + 8 * min(t & 127, 2u), me = (t >> 7) + 8;
    uint32_t pub, l;
    const uint32_t lnk = baton_wait_pub(st, sa + la + col + row, pub);
    asm volatile("ld.volatile.shared.u32 %0, [%1];" : "=r"(l) : "r"(la) : "memory");
    wg_fence();
    wg64_rs<true, 0, 0>(o0, fa, dWv);
    W(0, 1, 3, o0);
    asm volatile("{\n.reg .pred p;\nsetp.eq.u32 p, %0, %1;\n@p st.volatile.shared.u32 [%2], %3;\n}\n" ::"r"(l), "r"(me), "r"(la), "r"(lnk) : "memory");
    W(0, 4, 11, o0); wg_commit();
    wg64_rs<true, 0, 8192 / 16>(o1, fa, dWv);
    W(1, 1, 4, o1); wg_commit();
    wg_wait1(); pack_slice<false>(h, o0, nz);
    W_STAGE(1, o1);
    W(1, 9, 10, o1);
    send_slice(tm, slot, col, row, 0);
    wg_fence();
    W(1, 11, 11, o1); wg_commit();
    W(2, 0, 4, o2); wg_commit();
    wg_wait1(); pack_slice<false>(h, o1, nz);
    W_STAGE(2, o2);
    W(2, 9, 9, o2);
    asm volatile("{\n.reg .pred p;\nsetp.ne.u32 p, %0, %1;\n@p bar.arrive %0, 256;\n}\n" ::"r"(lnk), "r"(me) : "memory");
    wg_fence();
    W(2, 10, 11, o2); wg_commit();
    send_slice(tm, slot, col, row, 1);
    wg_wait0(); pack_slice<true>(h, o2, nz);
    fence_regs(fa);
#pragma unroll
    for (int i = 0; i < 4; i++) stage_part(sa, 2, h, i);
    send_slice(tm, slot, col, row, 2);
    bulk_commit();
    bulk_wait_read();
}
#undef W
#undef W_STAGE

__global__ void __launch_bounds__(kThreads, 1)
swin_attn_kernel(const __nv_bfloat16* __restrict__ wqkv, const __nv_bfloat16* __restrict__ wo, Scratch* __restrict__ sc, void* out, const int G,
                 const __grid_constant__ OutMaps tmo, const __grid_constant__ CUtensorMap tmx, const __grid_constant__ CUtensorMap tmp, const __grid_constant__ CUtensorMap tmc) {
    extern __shared__ uint8_t smem_raw[];
    constexpr uint32_t sbase = kSmemBase;
    const int tid = threadIdx.x, lane = tid & 31;

    FoldRegs fq;
#pragma unroll
    for (int j = 0; j < 6; j++) {
        asm volatile("" : "=r"(fq.B0[j].x), "=r"(fq.B0[j].y), "=r"(fq.B0[j].z), "=r"(fq.B0[j].w));
        asm volatile("" : "=r"(fq.B1[j].x), "=r"(fq.B1[j].y), "=r"(fq.B1[j].z), "=r"(fq.B1[j].w));
    }
#pragma unroll
    for (int j = 0; j < 48; j++) asm volatile("" : "=r"(fq.A[j]));
    {
        const int t = blockIdx.x + (tid & 32 ? G : 0);
        if (tid < 64 && t < kTiles) fold_load_qk(fq, wqkv, t, lane);
    }
    __syncwarp();
    uint32_t epoch;
    asm volatile("ld.relaxed.gpu.global.u32 %0, [%1];" : "=r"(epoch)
                 : "l"(reinterpret_cast<const char*>(sc->epoch) + (smem_u32(smem_raw) - kSmemBase)) : "memory");
    if (smem_u32(smem_raw) != kSmemBase) __trap();
    const uint32_t warpu = __reduce_or_sync(0xffffffffu, (uint32_t)tid >> 5), wgu = warpu >> 2;
    const int warp = (int)warpu, wg = (int)wgu;
    const int ftile = blockIdx.x + (warp & 1) * G;
    if (warp == 3) {
        const uint32_t i = blockIdx.x + G * (lane & 15);
        const char* p = lane < 16 ? (const char*)wo + i * 128 : (const char*)wqkv + i * 128 + (i / 3 + 1) * 768;
        if (i < 576) asm volatile("prefetch.global.L2 [%0];" ::"l"(p) : "memory");
    }
    if (warp == 10) {
        if (lane == 0) {
#pragma unroll
            for (int w = 0; w < kNWG; w++) {
                mbar_init(sbase + kOffBar + 8 * w, 1);
#pragma unroll
                for (int c = 0; c < 3; c++) mbar_init(bar_x(w, c), 1);
            }
            asm volatile("fence.mbarrier_init.release.cluster;" ::: "memory");
        }
        __syncwarp();
        asm volatile("bar.arrive 11, 384;" ::: "memory");
        if (lane == 0) {
            const uint32_t t0 = (uint32_t)clock64() + kPaceStart + ((blockIdx.x * 37) & 63) * kPaceSpread / 64;
#pragma unroll 1
            for (int i = 0; i < 3 * kNWG; i++) {
                while ((int)((uint32_t)clock64() - t0) < (i < 3 ? i * kPaceStep0 : kPaceMid + (i - 3) * kPaceStep)) {}
                const int w = i / 3, c = i % 3;
                mbar_expect_tx(bar_x(w, c), 8192);
                tma_load_x_chunk(sbase + kOffX + w * kXBytes + c * 8192, &tmc, bar_x(w, c), w * G + blockIdx.x, c);
            }
#pragma unroll 1
            for (int i = 0; i < kPfInit; i++) {
                while ((int)((uint32_t)clock64() - t0) < kPacePf + i * kPaceStepPf) {}
                prefetch_x(&tmp, (kNWG + i) * G + blockIdx.x);
            }
        }
    }
    if (warp < 3) {
        for (int t = ftile;;) {
            const bool on = warp < 2 && t < kTiles;
            fold_compute_store<false>(fq, sc, t, lane, epoch, on, G >> 16);
            t += 2 * G;
            if (__builtin_expect(warp == 2 || t >= kTiles, 1)) break;
            fold_load_qk(fq, wqkv, t, lane);
        }
    }
    if (warp < 4) {
        asm volatile("bar.sync 11, 384;" ::: "memory");
    } else if (warp == 4) {
        if (lane == 0) {
            asm volatile("st.shared.v4.u32 [%0], {9, 0, 8, 0};\nst.shared.v4.u32 [%0 + 16], {8, 0, 0, 0};" ::"r"(kLink) : "memory");
            asm volatile("st.shared.v2.u64 [%0], {%1, %2};" ::"r"(kScAddr), "l"(sc), "l"(out) : "memory");
            mbar_init(bar_m(0), 1);
            mbar_init(bar_m(1), 1);
            mbar_init(bar_m(2), 1);
            asm volatile("fence.mbarrier_init.release.cluster;" ::: "memory");
        }
        __syncwarp();
        asm volatile("bar.arrive 12, 128;" ::: "memory");
        uint32_t v;
        asm volatile("ld.relaxed.gpu.global.u32 %0, [%1];" : "=r"(v) : "l"(sc->cnt_m) : "memory");
        asm volatile("bar.sync 11, 384;" ::: "memory");
        { const uint32_t t0 = (uint32_t)clock64(); while ((uint32_t)clock64() - t0 < kPollDelay) {} }
        if (lane == 0) {
            uint32_t spins = 0;
            while (v < kMqkHint) {
                asm volatile("ld.relaxed.gpu.global.u32 %0, [%1];" : "=r"(v) : "l"(sc->cnt_m) : "memory");
                if (++spins > (1u << 22)) __trap();
            }
            const uint32_t par = epoch & 1;
            m_load(sc, 0, par); m_load(sc, 1, par); m_load(sc, 2, par);
        }
    } else if (warp == 11) {
        if (lane == 0) {
            mbar_init(kBarV, 1);
            asm volatile("fence.mbarrier_init.release.cluster;" ::: "memory");
        }
        __syncwarp();
        asm volatile("bar.sync 11, 384;" ::: "memory");
        if (lane == 0) {
            uint32_t v, spins = 0;
            do {
                asm volatile("ld.relaxed.gpu.global.u32 %0, [%1];" : "=r"(v) : "l"(sc->cnt_v) : "memory");
                if (++spins > (1u << 22)) __trap();
            } while (v < kTiles);
            uint32_t ok = 0, n = 0;
            while (!ok && ++n < 64)
                asm volatile("{\n.reg .pred p;\nmbarrier.try_wait.parity.shared::cta.b64 p, [%1], 0;\nselp.b32 %0, 1, 0, p;\n}\n" : "=r"(ok) : "r"(bar_m(2)) : "memory");
            v_load(sc, epoch & 1);
        }
    } else if (warp == 10) {
    } else if (warp >= 8) {
        asm volatile("bar.arrive 11, 384;" ::: "memory");
        if (warp == 9) { const uint32_t t0 = (uint32_t)clock64(); while ((uint32_t)clock64() - t0 < kWvoDelay) {} }
        FoldRegs fr;
        for (int t = G - 1 - blockIdx.x + (warp & 1) * G; t < kTiles; t += 2 * G) {
            fold_load_vo(fr, wqkv, wo, t, lane);
            fold_compute_store<true>(fr, sc, t, lane, epoch, 1, G >> 16);
        }
    } else {
        asm volatile("bar.arrive 11, 384;" ::: "memory");
        if (lane == 0) asm volatile("prefetch.tensormap [%0];" ::"l"(warp == 5 ? &tmo.m[0] : warp == 6 ? &tmo.m[1] : &tmx) : "memory");
        if (lane == 0 && warp == 5) asm volatile("prefetch.tensormap [%0];" ::"l"(&tmo.m[2]) : "memory");
        asm volatile("bar.sync 12, 128;" ::: "memory");
    }
    __syncwarp();
    if (wg == 1) m_check(sc, epoch & 1);
    uint4 hv[12];
#pragma unroll
    for (int a = 0; a < 12; a++) asm volatile("" : "=r"(hv[a].x), "=r"(hv[a].y), "=r"(hv[a].z), "=r"(hv[a].w));

    constexpr uint32_t dWm = ((sbase + kOffWm) >> 4) | (1u << 16);
    constexpr uint32_t dWv = ((sbase + kOffWv) >> 4) | (1u << 16);
    const float cs = 0.07216878364870322f * 1.4426950408889634f;
    if (wg == 2) asm volatile("bar.sync 13, 128;" ::: "memory");
    mbar_wait(bar_x(wg, 0), 0);

    uint32_t st = (uint32_t)(wg * G + blockIdx.x) << 17 | kFirst | kPhase | (wg == 0 ? kSolo | kVeryFirst | (epoch & 1) << 4 : 0);

    while (true) {
        float acc[96];
        uint32_t fa[48];
        const uint32_t dX = ((sbase + kOffX + wg_uniform() * kXBytes) >> 4) | (1u << 16);
        uint32_t ticket = 0;
        uint32_t lnk = baton_wait(st, 0);
        while (true) {
            const bool very_first = st & kVeryFirst;
            Gemm1<11>::run(acc, dX, dWm, very_first, st);
            wg_commit();
            if (!very_first) { baton_pass(lnk, st); break; }
            __syncwarp();
            if (m_agree(1)) break;
            wg_wait0();
            asm volatile("bar.arrive 7, 256;" ::: "memory");
            st ^= kRound;
        }
        draw_ticket(ticket);
        if (!(st & kFirst)) {
            const uint32_t w4 = warp4_uniform();
            const uint32_t slot = sbase + kOffStage + w4 * 2048;
            const int col = (st_out(st) & 63) * 8, row = (st_out(st) >> 6) * 8 + 2 * w4;
            store_round<0>(hv, slot, tmo.m, col, row);
            bulk_wait_read();
            __syncwarp();
            store_round<1>(hv, slot, tmo.m, col, row);
            bulk_wait_read();
            __syncwarp();
            store_round<2>(hv, slot, tmo.m, col, row);
        }
        __syncwarp();
        wg_wait0();
        fence_regs(acc);
#pragma unroll
        for (int i = 0; i < 48; i++) fa[i] = pack_bf16(acc[2 * i], acc[2 * i + 1]);

        float s[32];
        fence_regs(fa);
        if (!(st & kFirst)) publish(ticket);
        uint32_t pub, marks;
        lnk = baton_wait_pub(st, fa[47], pub);
        asm volatile("ld.volatile.shared.u32 %0, [%1];" : "=r"(marks) : "r"(kMarks) : "memory");
        wg_fence();
        Gemm2<11>::run(s, fa, dX, lnk, st);
        wg_commit();
        uint32_t mine = pub;
        if (st & kFirst) {
            publish(ticket);
            mine = ticket;
        }
        if (mine == kNWin - 1 && (tid_now() & 127) == 0) reset_for_next_launch();
        __syncwarp();
        const uint32_t alone = __reduce_or_sync(0xffffffffu, pub >= (uint32_t)(kNWin - kNWG * G) && ((marks | 1u << 8 * (tid_now() >> 7)) ^ (st & kFirst)) == 0x10101);
        wg_wait0();
        fence_regs(s);
        fence_regs(fa);

        uint32_t pa[16];
        {
            float a0[8], a1[8];
#pragma unroll
            for (int j = 0; j < 8; j++) { a0[j] = fmaxf(s[4 * j], s[4 * j + 1]); a1[j] = fmaxf(s[4 * j + 2], s[4 * j + 3]); }
#pragma unroll
            for (int d = 4; d > 0; d >>= 1)
#pragma unroll
                for (int j = 0; j < d; j++) { a0[j] = fmaxf(a0[j], a0[j + d]); a1[j] = fmaxf(a1[j], a1[j + d]); }
            float m0 = a0[0], m1 = a1[0];
            m0 = fmaxf(m0, __shfl_xor_sync(0xffffffffu, m0, 1));
            m1 = fmaxf(m1, __shfl_xor_sync(0xffffffffu, m1, 1));
            m0 = fmaxf(m0, __shfl_xor_sync(0xffffffffu, m0, 2));
            m1 = fmaxf(m1, __shfl_xor_sync(0xffffffffu, m1, 2));
            m0 *= cs; m1 *= cs;
            float l0 = 0.f, l1 = 0.f;
#pragma unroll
            for (int j = 0; j < 8; j++) {
                s[4 * j]     = ex2(fmaf(s[4 * j], cs, -m0));
                s[4 * j + 1] = ex2(fmaf(s[4 * j + 1], cs, -m0));
                s[4 * j + 2] = ex2(fmaf(s[4 * j + 2], cs, -m1));
                s[4 * j + 3] = ex2(fmaf(s[4 * j + 3], cs, -m1));
                l0 += s[4 * j] + s[4 * j + 1];
                l1 += s[4 * j + 2] + s[4 * j + 3];
            }
            l0 += __shfl_xor_sync(0xffffffffu, l0, 1);
            l1 += __shfl_xor_sync(0xffffffffu, l1, 1);
            l0 += __shfl_xor_sync(0xffffffffu, l0, 2);
            l1 += __shfl_xor_sync(0xffffffffu, l1, 2);
            const float r0 = rcp(l0), r1 = rcp(l1);
#pragma unroll
            for (int j = 0; j < 8; j++) {
                pa[2 * j]     = pack_bf16(s[4 * j] * r0, s[4 * j + 1] * r0);
                pa[2 * j + 1] = pack_bf16(s[4 * j + 2] * r1, s[4 * j + 3] * r1);
            }
        }

        fence_regs(pa);
        if (alone) {
            finish_alone(pa, dX + (((8192u >> 4) - 1) << 16), dWv, tmo.m, st);
            return;
        }
        lnk = baton_wait_pub(st, pa[15], pub);
        if ((st & kFirst) && tid_now() == 0) set_link(1, 10);
        wg_fence();
        Gemm3<3>::run(acc, pa, dX + (((8192u >> 4) - 1) << 16));
        wg_commit();
        asm volatile("{\n.reg .pred p;\nsetp.ge.u32 p, %0, %1;\n@p st.volatile.shared.u8 [%2], %3;\n}\n"
                     ::"r"(pub), "r"(kNWin - kNWG * G), "r"(kMarks + (tid_now() >> 7)), "r"(1) : "memory");
        baton_pass(lnk, st);
        const int nxt = (int)(__reduce_or_sync(0xffffffffu, pub) + kNWG * G);
        wg_wait0();
        fence_regs(acc);
        fence_regs(pa);

        if (((tid_now() >> 5) & 3) == 0 && nxt < kNWin) {
            asm volatile("bar.sync %0, 128;" ::"r"((tid_now() >> 7) + 1) : "memory");
            if (elect_one()) {
                const uint32_t wgl = tid_now() >> 7;
                const uint32_t bar = sbase + kOffBar + 8 * wgl;
                mbar_expect_tx(bar, kXBytes);
                tma_load_x(sbase + kOffX + wgl * kXBytes, &tmx, bar, nxt);
            }
            __syncwarp();
        } else {
            asm volatile("bar.arrive %0, 128;" ::"r"((tid_now() >> 7) + 1) : "memory");
        }
        if (st & kVeryFirst) v_check(st);
        fence_regs(acc);
#pragma unroll
        for (int i = 0; i < 48; i++) fa[i] = pack_bf16(acc[2 * i], acc[2 * i + 1]);

        asm volatile("st.volatile.shared.v4.b32 [%4], {%0, %1, %2, %3};"
                     :: "r"(fa[44]), "r"(fa[45]), "r"(fa[46]), "r"(fa[47]), "r"(sbase + kOffStash + (tid_now() & 127) * 16) : "memory");
        fence_regs(fa);
        if (((tid_now() >> 5) & 3) == 0 && nxt + kPfMin < kNWin) {
            if (elect_one()) {
                const int base = kNWG * G, t = nxt - base;
                const int hi = min(nxt + pf_lead(t, G), kNWin - 1);
                int lo = max(max(nxt - 1 + pf_lead(t - 1, G), nxt) + 1, base + kPfInit * G);
#pragma unroll 1
                for (; lo <= hi; lo++) prefetch_x(&tmp, lo);
            }
            __syncwarp();
        }
        if (nxt >= kNWin) {
            finish_last(fa, dWv, tmo.m, st);
            return;
        }
        lnk = baton_wait(st, fa[43]);
        wg_fence();
        Gemm4<0, 1>::run(acc, fa, dWv);
        wg_commit();
        Gemm4<2, 10>::run(acc, fa, dWv);
        wg_commit();
        wg_wait1();
        uint32_t fl[4];
        asm volatile("ld.volatile.shared.v4.b32 {%0, %1, %2, %3}, [%4];"
                     : "=r"(fl[0]), "=r"(fl[1]), "=r"(fl[2]), "=r"(fl[3]) : "r"(sbase + kOffStash + (tid_now() & 127) * 16) : "memory");
        wg_fence();
        wg192_rs<false, 0, koff(11, 24576)>(acc, fl, dWv);
        wg_commit();
        baton_pass(lnk, st);
        st = ((st ^ kPhase) & (kPhase | kSolo)) | st_win(st) << 4 | nxt << 17;
        uint32_t landed;
        asm volatile("{\n.reg .pred p;\nmbarrier.test_wait.parity.shared::cta.b64 p, [%1], %2;\nselp.b32 %0, 1, 0, p;\n}\n"
                     : "=r"(landed) : "r"(sbase + kOffBar + 8 * (tid_now() >> 7)), "r"(st & kPhase) : "memory");
        wg_wait0();
        fence_regs(acc);
        fence_regs(fa);
        fence_regs(fl);

#pragma unroll
        for (int a = 0; a < 6; a++)
#pragma unroll
            for (int r = 0; r < 2; r++)
                hv[2 * a + r] = make_uint4(pack_bf16(acc[16 * a + 2 * r], acc[16 * a + 2 * r + 1]), pack_bf16(acc[16 * a + 2 * r + 4], acc[16 * a + 2 * r + 5]),
                                           pack_bf16(acc[16 * a + 2 * r + 8], acc[16 * a + 2 * r + 9]), pack_bf16(acc[16 * a + 2 * r + 12], acc[16 * a + 2 * r + 13]));
        if (!landed) mbar_wait(sbase + kOffBar + 8 * (tid_now() >> 7), st & kPhase);
    }
}

typedef CUresult (*EncodeTiledFn)(CUtensorMap*, CUtensorMapDataType, cuuint32_t, void*, const cuuint64_t*,
                                  const cuuint64_t*, const cuuint32_t*, const cuuint32_t*, CUtensorMapInterleave,
                                  CUtensorMapSwizzle, CUtensorMapL2promotion, CUtensorMapFloatOOBfill);

}

extern "C" void kernel_launch(void* const* d_in, const int* in_sizes, int n_in, void* d_out, int out_size) {
    (void)in_sizes; (void)n_in; (void)out_size;
    const __nv_bfloat16* x    = (const __nv_bfloat16*)d_in[0];
    const __nv_bfloat16* wqkv = (const __nv_bfloat16*)d_in[1];
    const __nv_bfloat16* wo   = (const __nv_bfloat16*)d_in[2];

    static EncodeTiledFn encode = nullptr;
    static int num_sms = 0;
    static Scratch* scratch = nullptr;
    if (!encode) {
        void* fn = nullptr;
        cudaDriverEntryPointQueryResult qr;
        cudaGetDriverEntryPoint("cuTensorMapEncodeTiled", &fn, cudaEnableDefault, &qr);
        encode = (EncodeTiledFn)fn;
        cudaGetSymbolAddress((void**)&scratch, g_scratch);
        int dev = 0;
        cudaGetDevice(&dev);
        cudaDeviceGetAttribute(&num_sms, cudaDevAttrMultiProcessorCount, dev);
        cudaFuncSetAttribute(swin_attn_kernel, cudaFuncAttributeMaxDynamicSharedMemorySize, kSmemBytes);
    }
    CUtensorMap tmx;
    const cuuint64_t gdim[4] = {64, (cuuint64_t)kHW, (cuuint64_t)kHW, 3};
    const cuuint64_t gstr[3] = {(cuuint64_t)kC * 2, (cuuint64_t)kHW * kC * 2, 128};
    const cuuint32_t box[4] = {64, 8, 8, 3};
    const cuuint32_t estr[4] = {1, 1, 1, 1};
    encode(&tmx, CU_TENSOR_MAP_DATA_TYPE_BFLOAT16, 4, (void*)x, gdim, gstr, box, estr, CU_TENSOR_MAP_INTERLEAVE_NONE,
           CU_TENSOR_MAP_SWIZZLE_128B, CU_TENSOR_MAP_L2_PROMOTION_NONE, CU_TENSOR_MAP_FLOAT_OOB_FILL_NONE);

    CUtensorMap tmp;
    const cuuint64_t pdim[3] = {(cuuint64_t)kC, (cuuint64_t)kHW, (cuuint64_t)kHW};
    const cuuint64_t pstr[2] = {(cuuint64_t)kC * 2, (cuuint64_t)kHW * kC * 2};
    const cuuint32_t pbox[3] = {(cuuint32_t)kC, 8, 8};
    encode(&tmp, CU_TENSOR_MAP_DATA_TYPE_BFLOAT16, 3, (void*)x, pdim, pstr, pbox, estr, CU_TENSOR_MAP_INTERLEAVE_NONE,
           CU_TENSOR_MAP_SWIZZLE_NONE, CU_TENSOR_MAP_L2_PROMOTION_NONE, CU_TENSOR_MAP_FLOAT_OOB_FILL_NONE);
    CUtensorMap tmc;
    const cuuint32_t boxc[4] = {64, 8, 8, 1};
    encode(&tmc, CU_TENSOR_MAP_DATA_TYPE_BFLOAT16, 4, (void*)x, gdim, gstr, boxc, estr, CU_TENSOR_MAP_INTERLEAVE_NONE,
           CU_TENSOR_MAP_SWIZZLE_128B, CU_TENSOR_MAP_L2_PROMOTION_NONE, CU_TENSOR_MAP_FLOAT_OOB_FILL_NONE);
    OutMaps tmo;
    const cuuint32_t boxo[4] = {64, 8, 1, 2};
    encode(&tmo.m[0], CU_TENSOR_MAP_DATA_TYPE_BFLOAT16, 4, d_out, gdim, gstr, boxo, estr, CU_TENSOR_MAP_INTERLEAVE_NONE,
           CU_TENSOR_MAP_SWIZZLE_128B, CU_TENSOR_MAP_L2_PROMOTION_NONE, CU_TENSOR_MAP_FLOAT_OOB_FILL_NONE);
    const cuuint64_t odim[4] = {64, (cuuint64_t)kHW, (cuuint64_t)kHW, 2};
    const cuuint64_t ostr[3] = {(cuuint64_t)kC * 2, (cuuint64_t)kHW * kC * 2, (cuuint64_t)kHW * kC * 2 - 256};
    encode(&tmo.m[1], CU_TENSOR_MAP_DATA_TYPE_BFLOAT16, 4, (char*)d_out + 256, odim, ostr, boxo, estr, CU_TENSOR_MAP_INTERLEAVE_NONE,
           CU_TENSOR_MAP_SWIZZLE_128B, CU_TENSOR_MAP_L2_PROMOTION_NONE, CU_TENSOR_MAP_FLOAT_OOB_FILL_NONE);
    const cuuint32_t boxs[4] = {64, 8, 2, 1};
    encode(&tmo.m[2], CU_TENSOR_MAP_DATA_TYPE_BFLOAT16, 4, d_out, gdim, gstr, boxs, estr, CU_TENSOR_MAP_INTERLEAVE_NONE,
           CU_TENSOR_MAP_SWIZZLE_128B, CU_TENSOR_MAP_L2_PROMOTION_NONE, CU_TENSOR_MAP_FLOAT_OOB_FILL_NONE);
    swin_attn_kernel<<<num_sms, kThreads, kSmemBytes, cudaStreamPerThread>>>(wqkv, wo, scratch, d_out, num_sms, tmo, tmx, tmp, tmc);
}
```
